```python
import torch

def _softmax(x, axis=-1):
    return torch.softmax(x, dim=axis)
def _gelu(x):
    return torch.nn.functional.gelu(x, approximate="tanh")
def _silu(x):
    return torch.nn.functional.silu(x)
def _sigmoid(x):
    return torch.sigmoid(x)
def _layernorm(x, axis=-1, eps=1e-5):
    m = x.mean(dim=axis, keepdim=True)
    v = x.var(dim=axis, keepdim=True, unbiased=False)
    return (x - m) / torch.sqrt(v + eps)
def _scatter_add(tgt, idx, src, axis=0):
    return tgt.clone().index_add_(axis, idx, src)
def _segment_sum(src, seg, n):
    out = torch.zeros((n,) + src.shape[1:], dtype=src.dtype)
    return out.index_add_(0, seg, src)
def _pad(x, pw):
    flat = tuple(v for pair in reversed(pw) for v in pair)
    return torch.nn.functional.pad(x, flat)

kernel_name = 'standalone__cheap_equivariant_egnn__graph'

def setup_inputs():

    _w = (lambda a: (lambda t: t.to(torch.bfloat16) if t.is_floating_point() else t)(torch.as_tensor(a)))
    N, deg, D, De = 10000, 16, 256, max(4, 1)
    E = N * deg
    return {
        "h": _w((lambda *s: torch.randn(*s, dtype=torch.bfloat16) * 0.2)(N, D)),
        "pos": _w((lambda *s: torch.randn(*s, dtype=torch.bfloat16) * 0.4)(N, 3)),
        "e_attr": _w((lambda *s: torch.randn(*s, dtype=torch.bfloat16) * 0.4)(E, De)),
        "src": _w((lambda lo, hi, *s: torch.randint(lo, hi, s))(0, N, E).to(torch.int64)),
        "dst": _w((lambda lo, hi, *s: torch.randint(lo, hi, s))(0, N, E).to(torch.int64)),
        "w_e": _w(0.1 * (lambda *s: torch.randn(*s, dtype=torch.bfloat16) * 0.4)(2 * D + 1 + De, D)),
        "w_x": _w(0.1 * (lambda *s: torch.randn(*s, dtype=torch.bfloat16) * 0.2)(D, 1)),
        "w_h": _w(0.1 * (lambda *s: torch.randn(*s, dtype=torch.bfloat16) * 0.2)(2 * D, D)),
    }

def reference(h, pos, e_attr, src, dst, w_e, w_x, w_h):
    N, D = h.shape[0], h.shape[1]
    diff = pos[dst] - pos[src]
    dist2 = torch.sum(diff * diff, axis=-1, keepdims=True)
    e_in = torch.concatenate([h[dst], h[src], dist2, e_attr], axis=-1)
    m_ij = _silu(e_in @ w_e)
    coord_scale = m_ij @ w_x
    pos_new = pos + _segment_sum(diff * coord_scale, dst, N)
    m_i = _segment_sum(m_ij, dst, N)
    h_new = h + _silu(torch.concatenate([h, m_i], axis=-1) @ w_h)
    return h_new, pos_new
```

```cpp
#include <cuda_runtime.h>
#include <cuda_bf16.h>
#include <cuda.h>
#include <stdint.h>

namespace {

constexpr int NN = 10000, NE = 160000, NCL = 66, RPC = 152, NCTA = 132, EPC = 1216, NTH = 512;
constexpr int NSLOT = 64, RTOT = 3200, RCAP = 3136;
constexpr int OFF_RX = 0, OFF_RH = 20480, OFF_W0 = 98304, OFF_W1 = 163840, OFF_MISC = 229376, SMEM_TOTAL = 232448;
constexpr int ATOM = RPC * 128;
constexpr int PL = 224 * 128;
constexpr int OFF_STM = OFF_W1 + 60416;
constexpr int OFF_META = OFF_W1 + RTOT * 16;
constexpr int OFF_PP = OFF_W1 + 2 * ATOM + 20480;
constexpr int M_BAR = OFF_MISC;
constexpr int M_CC = OFF_MISC + 256;
constexpr int M_CO = OFF_MISC + 576;
constexpr int M_NC = OFF_MISC + 896;
constexpr int M_CUR = OFF_MISC + 1536;
constexpr int M_END = OFF_MISC + 2176;
constexpr int M_NE = OFF_MISC + 2816;
constexpr int BAR_H = 0, BAR_W2 = 4, BAR_WH1 = 8, BAR_W1 = 12, BAR_WH2 = 16, BAR_POS = 20, BAR_M = 21;
constexpr uint32_t SPIN_LIMIT = 1u << 22;

__device__ uint4 g_B[2 * NN * 32];
__device__ uint4 g_C[NCTA * 5 * NTH];
__device__ uint4 g_rec[NCTA * EPC];
__device__ uint32_t g_meta[NCTA * EPC];
__device__ uint32_t g_flagP[NCL * NCTA];
__device__ uint32_t g_flagB[NCTA];
__device__ uint32_t g_epoch;
__device__ uint4 g_Asave[NCTA * RPC * 16];
__device__ float g_macc[NCTA * RPC * 128];
#define TS(i)

struct Params {
    const uint4* h; const unsigned short* pos; const uint2* ea; const int* src; const int* dst;
    const uint4* we; const uint4* wx; uint4* out_h; unsigned short* out_pos; char* B;
};

__device__ __forceinline__ uint32_t hfma2(uint32_t a, uint32_t b, uint32_t c) { uint32_t r; asm("fma.rn.bf16x2 %0,%1,%2,%3;" : "=r"(r) : "r"(a), "r"(b), "r"(c)); return r; }
__device__ __forceinline__ uint32_t hmul2(uint32_t a, uint32_t b) { uint32_t r; asm("mul.rn.bf16x2 %0,%1,%2;" : "=r"(r) : "r"(a), "r"(b)); return r; }
__device__ __forceinline__ uint32_t hadd2(uint32_t a, uint32_t b) { uint32_t r; asm("add.rn.bf16x2 %0,%1,%2;" : "=r"(r) : "r"(a), "r"(b)); return r; }
__device__ __forceinline__ uint32_t hsub2(uint32_t a, uint32_t b) { uint32_t r; asm("sub.rn.bf16x2 %0,%1,%2;" : "=r"(r) : "r"(a), "r"(b)); return r; }
__device__ __forceinline__ uint32_t hfma2_l(uint32_t a, uint32_t b, uint32_t c) { uint32_t r; asm("{.reg .b16 l,h; .reg .b32 t; mov.b32 {l,h},%2; mov.b32 t,{l,l}; fma.rn.bf16x2 %0,%1,t,%3;}" : "=r"(r) : "r"(a), "r"(b), "r"(c)); return r; }
__device__ __forceinline__ uint32_t hfma2_h(uint32_t a, uint32_t b, uint32_t c) { uint32_t r; asm("{.reg .b16 l,h; .reg .b32 t; mov.b32 {l,h},%2; mov.b32 t,{h,h}; fma.rn.bf16x2 %0,%1,t,%3;}" : "=r"(r) : "r"(a), "r"(b), "r"(c)); return r; }
__device__ __forceinline__ uint32_t tanh2(uint32_t a) { uint32_t r; asm("tanh.approx.bf16x2 %0,%1;" : "=r"(r) : "r"(a)); return r; }
__device__ __forceinline__ float tanh1(float x) { float r; asm("tanh.approx.f32 %0,%1;" : "=f"(r) : "f"(x)); return r; }
__device__ __forceinline__ uint32_t pack2(float lo, float hi) { uint32_t r; asm("cvt.rn.bf16x2.f32 %0,%1,%2;" : "=r"(r) : "f"(hi), "f"(lo)); return r; }
__device__ __forceinline__ float blo(uint32_t v) { return __uint_as_float(v << 16); }
__device__ __forceinline__ float bhi(uint32_t v) { return __uint_as_float(v & 0xffff0000u); }
template <int OFF> __device__ __forceinline__ uint4 ldg_row(uint32_t lo, uint32_t hi) {
    uint4 v; asm volatile("{.reg .b64 a; mov.b64 a,{%4,%5}; ld.global.L1::no_allocate.v4.u32 {%0,%1,%2,%3},[a+%6];}"
                          : "=r"(v.x), "=r"(v.y), "=r"(v.z), "=r"(v.w) : "r"(lo), "r"(hi), "n"(OFF)); return v; }
template <int OFF> __device__ __forceinline__ uint4 lds128(uint32_t a) { uint4 v; asm volatile("ld.shared.v4.u32 {%0,%1,%2,%3},[%4+%5];" : "=r"(v.x), "=r"(v.y), "=r"(v.z), "=r"(v.w) : "r"(a), "n"(OFF)); return v; }
template <int OFF> __device__ __forceinline__ uint32_t lds32(uint32_t a) { uint32_t v; asm volatile("ld.shared.u32 %0,[%1+%2];" : "=r"(v) : "r"(a), "n"(OFF)); return v; }
template <int OFF> __device__ __forceinline__ uint32_t lds16(uint32_t a) { uint32_t v; asm volatile("ld.shared.u16 %0,[%1+%2];" : "=r"(v) : "r"(a), "n"(OFF)); return v; }
template <int OFF> __device__ __forceinline__ void sts128(uint32_t a, uint32_t x, uint32_t y, uint32_t z, uint32_t w) { asm volatile("st.shared.v4.u32 [%0+%5],{%1,%2,%3,%4};" ::"r"(a), "r"(x), "r"(y), "r"(z), "r"(w), "n"(OFF) : "memory"); }
template <int OFF> __device__ __forceinline__ void sts32(uint32_t a, uint32_t x) { asm volatile("st.shared.u32 [%0+%2],%1;" ::"r"(a), "r"(x), "n"(OFF) : "memory"); }
__device__ __forceinline__ uint32_t atoms_inc(uint32_t a) { uint32_t r; asm volatile("atom.shared.add.u32 %0,[%1],1;" : "=r"(r) : "r"(a) : "memory"); return r; }
__device__ __forceinline__ void reds_inc(uint32_t a) { asm volatile("red.shared.add.u32 [%0],1;" ::"r"(a) : "memory"); }
__device__ __forceinline__ uint32_t ld_acq(const uint32_t* p) { uint32_t v; asm volatile("ld.acquire.gpu.global.u32 %0,[%1];" : "=r"(v) : "l"(p) : "memory"); return v; }
__device__ __forceinline__ void st_rel(uint32_t* p, uint32_t v) { asm volatile("st.release.gpu.global.u32 [%0],%1;" ::"l"(p), "r"(v) : "memory"); }
__device__ __forceinline__ uint32_t ldg_cg(const uint32_t* p) { uint32_t v; asm volatile("ld.global.cg.u32 %0,[%1];" : "=r"(v) : "l"(p) : "memory"); return v; }
__device__ __forceinline__ void mbar_init(uint32_t bar, uint32_t cnt) { asm volatile("mbarrier.init.shared::cta.b64 [%0],%1;" ::"r"(bar), "r"(cnt) : "memory"); }
__device__ __forceinline__ void mbar_expect(uint32_t bar, uint32_t bytes) { asm volatile("mbarrier.arrive.expect_tx.shared::cta.b64 _,[%0],%1;" ::"r"(bar), "r"(bytes) : "memory"); }
__device__ __forceinline__ void mbar_wait(uint32_t bar) {
    asm volatile("{.reg .pred p; .reg .u32 c; mov.u32 c,0;\n"
                 "LW: mbarrier.try_wait.parity.shared::cta.b64 p,[%0],0; @p bra LD; add.u32 c,c,1; setp.lt.u32 p,c,%1; @p bra LW;\n"
                 "LD: }" ::"r"(bar), "n"(SPIN_LIMIT) : "memory");
}
__device__ __forceinline__ void tma2d(uint32_t dst, const CUtensorMap* m, int c0, int c1, uint32_t bar) {
    asm volatile("cp.async.bulk.tensor.2d.shared::cluster.global.mbarrier::complete_tx::bytes [%0],[%1,{%3,%4}],[%2];"
                 ::"r"(dst), "l"((uint64_t)m), "r"(bar), "r"(c0), "r"(c1) : "memory");
}
__device__ __forceinline__ void load_w(uint32_t dst, const CUtensorMap* m, int col, int row, uint32_t bar) {
    mbar_expect(bar, 16384); tma2d(dst, m, col, row, bar); tma2d(dst + 8192, m, col + 64, row, bar);
}
__device__ __forceinline__ void fence_async() { asm volatile("fence.proxy.async.shared::cta;" ::: "memory"); }
__device__ __forceinline__ void bar_wg(int wg) { asm volatile("bar.sync %0,128;" ::"r"(wg + 1) : "memory"); }
__device__ __forceinline__ void wg_fence() { asm volatile("wgmma.fence.sync.aligned;" ::: "memory"); }
__device__ __forceinline__ void wg_commit() { asm volatile("wgmma.commit_group.sync.aligned;" ::: "memory"); }
template <int N_> __device__ __forceinline__ void wg_wait() { asm volatile("wgmma.wait_group.sync.aligned %0;" ::"n"(N_) : "memory"); }
__device__ __forceinline__ uint64_t mkdesc(uint32_t addr) { return (uint64_t)((addr & 0x3FFFF) >> 4) | (1ull << 16) | (64ull << 32) | (1ull << 62); }
#define R8(o) "+f"(d[o]), "+f"(d[o + 1]), "+f"(d[o + 2]), "+f"(d[o + 3]), "+f"(d[o + 4]), "+f"(d[o + 5]), "+f"(d[o + 6]), "+f"(d[o + 7])
template <int SC> __device__ __forceinline__ void wgmma80(float* d, uint64_t da, uint64_t db) {
    asm volatile("wgmma.mma_async.sync.aligned.m64n80k16.f32.bf16.bf16 {%0,%1,%2,%3,%4,%5,%6,%7,%8,%9,%10,%11,%12,%13,%14,%15,%16,%17,%18,%19,"
                 "%20,%21,%22,%23,%24,%25,%26,%27,%28,%29,%30,%31,%32,%33,%34,%35,%36,%37,%38,%39},%40,%41,%42,1,1,1,0;"
                 : R8(0), R8(8), R8(16), R8(24), R8(32) : "l"(da), "l"(db), "n"(SC));
}
template <bool FIRST> __device__ __forceinline__ void gemm_chunk(float* d, uint32_t wAddr, uint32_t xAddr) {
    const uint64_t da = mkdesc(wAddr), db = mkdesc(xAddr);
    wg_fence();
    wgmma80<FIRST ? 0 : 1>(d, da, db);
    wgmma80<1>(d, da + 128, db + 2); wgmma80<1>(d, da + 256, db + 4); wgmma80<1>(d, da + 384, db + 6);
    wg_commit();
}
__device__ __forceinline__ void pin40(float* d) {
#pragma unroll
    for (int i = 0; i < 40; i++) asm volatile("" : "+f"(d[i])::"memory");
}
__device__ __forceinline__ void stsm4t(uint32_t a, uint32_t x, uint32_t y, uint32_t z, uint32_t w) {
    asm volatile("stmatrix.sync.aligned.m8n8.x4.trans.shared.b16 [%0],{%1,%2,%3,%4};" ::"r"(a), "r"(x), "r"(y), "r"(z), "r"(w) : "memory");
}
template <int I> struct IC { static constexpr int v = I; };
template <int N_, class F> __device__ __forceinline__ void sfor(F f) { if constexpr (N_ > 0) { sfor<N_ - 1>(f); f(IC<N_ - 1>{}); } }

__device__ __forceinline__ void scan_nodes(uint32_t sb, int lane) {
    uint32_t c[5], s = 0;
#pragma unroll
    for (int i = 0; i < 5; i++) { c[i] = lds32<M_NC>(sb + (lane * 5 + i) * 4); s += c[i]; }
    uint32_t x = s;
#pragma unroll
    for (int o = 1; o < 32; o <<= 1) { uint32_t y = __shfl_up_sync(~0u, x, o); if (lane >= o) x += y; }
    uint32_t b = x - s;
#pragma unroll
    for (int i = 0; i < 5; i++) { sts32<M_CUR>(sb + (lane * 5 + i) * 4, b); b += c[i]; sts32<M_END>(sb + (lane * 5 + i) * 4, b); }
    if (lane == 31) sts32<M_NE>(sb, x);
}
__device__ __forceinline__ void place_one(uint32_t sb, uint32_t meta, const uint4* rec) {
    const uint32_t n4 = (meta >> 23) * 4;
    const uint32_t p = atoms_inc(sb + M_CUR + n4);
    if (p + 1 == lds32<M_END>(sb + n4)) meta |= 0x80000000u;
    asm volatile("cp.async.cg.shared.global [%0],[%1],16;" ::"r"(sb + OFF_W1 + p * 16), "l"(rec) : "memory");
    sts32<OFF_META>(sb + p * 4, meta);
}

__global__ void __cluster_dims__(2, 1, 1) __launch_bounds__(NTH, 1)
egnn_kernel(const __grid_constant__ CUtensorMap tmH, const __grid_constant__ CUtensorMap tmWe,
            const __grid_constant__ CUtensorMap tmWh, const Params p) {
    extern __shared__ __align__(1024) unsigned char smem[];
    const uint32_t sb = (uint32_t)__cvta_generic_to_shared(smem);
    const int tid = threadIdx.x, lane = tid & 31, wid = __shfl_sync(~0u, tid >> 5, 0);
    const int cta = blockIdx.x, cl = cta >> 1, half = cta & 1, node0 = cl * RPC;
    const int wg = wid >> 2, w = wid & 3, mt = wg & 1, nh = wg >> 1;
    TS(0);
    if (tid == 0) {
#pragma unroll
        for (int i = 0; i < 22; i++) mbar_init(sb + M_BAR + i * 8, 1);
        asm volatile("fence.mbarrier_init.release.cluster;" ::: "memory");
        fence_async();
        mbar_expect(sb + M_BAR + BAR_POS * 8, NN * 6);
        asm volatile("cp.async.bulk.shared::cluster.global.mbarrier::complete_tx::bytes [%0],[%1],%2,[%3];"
                     ::"r"(sb + OFF_W1), "l"(p.pos), "n"(NN * 6), "r"(sb + M_BAR + BAR_POS * 8) : "memory");
#pragma unroll
        for (int k = 0; k < 4; k++) {
            mbar_expect(sb + M_BAR + (BAR_H + k) * 8, ATOM);
            tma2d(sb + OFF_RH + k * ATOM, &tmH, k * 64, node0, sb + M_BAR + (BAR_H + k) * 8);
            load_w(sb + OFF_W0 + k * 16384, &tmWe, half * 128, 256 + k * 64, sb + M_BAR + (BAR_W2 + k) * 8);
        }
        mbar_expect(sb + M_BAR + BAR_M * 8, 2 * ATOM);
    }
    int es[3], ed[3]; uint2 ee[3];
#pragma unroll
    for (int i = 0; i < 3; i++) {
        const int l = tid + i * NTH, e = cta * EPC + l; const bool ok = l < EPC && e < NE;
        ed[i] = ok ? __ldg(p.dst + e) : -1; es[i] = ok ? __ldg(p.src + e) : 0; ee[i] = ok ? __ldg(p.ea + e) : make_uint2(0, 0);
    }
    const uint32_t tag = (ldg_cg(&g_epoch) + 1) & 0x3ffu;
    if (tid < 80) sts32<M_CC>(sb + tid * 4, 0);
    if (tid >= 96 && tid < 256) sts32<M_NC>(sb + (tid - 96) * 4, 0);
    __syncthreads();
    uint32_t rk[3], ec[3], rz[3], rw[3];
#pragma unroll
    for (int i = 0; i < 3; i++) { ec[i] = (uint32_t)ed[i] / RPC; if (ed[i] >= 0) rk[i] = atoms_inc(sb + M_CC + ec[i] * 4); }
    TS(1);
    mbar_wait(sb + M_BAR + BAR_POS * 8);
#pragma unroll
    for (int i = 0; i < 3; i++) {
        if (ed[i] >= 0) {
            const uint32_t ad = sb + OFF_W1 + ed[i] * 6, as = sb + OFF_W1 + es[i] * 6;
            const uint32_t dx = hsub2(lds16<0>(ad), lds16<0>(as));
            const uint32_t dyz = hsub2(lds16<2>(ad) | (lds16<4>(ad) << 16), lds16<2>(as) | (lds16<4>(as) << 16));
            const uint32_t qx = hmul2(dx, dx), qyz = hmul2(dyz, dyz);
            rz[i] = __byte_perm(pack2((blo(qx) + blo(qyz)) + bhi(qyz), 0.f), dx, 0x5410);
            rw[i] = dyz;
        }
    }
    __syncthreads();
    if (wid == 0) {
        uint32_t c[3], s = 0;
#pragma unroll
        for (int i = 0; i < 3; i++) { c[i] = lane < 22 ? lds32<M_CC>(sb + (lane * 3 + i) * 4) : 0; s += c[i]; }
        uint32_t x = s;
#pragma unroll
        for (int o = 1; o < 32; o <<= 1) { uint32_t y = __shfl_up_sync(~0u, x, o); if (lane >= o) x += y; }
        uint32_t b = x - s;
#pragma unroll
        for (int i = 0; i < 3; i++) { if (lane < 22) sts32<M_CO>(sb + (lane * 3 + i) * 4, b); b += c[i]; }
    }
    __syncthreads();
#pragma unroll
    for (int i = 0; i < 3; i++) {
        if (ed[i] >= 0) {
            const uint32_t q = lds32<M_CO>(sb + ec[i] * 4) + rk[i];
            sts128<OFF_RX>(sb + q * 16, ee[i].x, ee[i].y, rz[i], rw[i]);
            sts32<OFF_STM>(sb + q * 4, (uint32_t)es[i] | ((ed[i] - ec[i] * RPC) << 23));
        }
    }
    __syncthreads();
#pragma unroll
    for (int i = 0; i < 3; i++) {
        if (ed[i] >= 0) {
            const int l = tid + i * NTH;
            g_rec[cta * EPC + l] = lds128<OFF_RX>(sb + l * 16);
            g_meta[cta * EPC + l] = lds32<OFF_STM>(sb + l * 4);
        }
    }
    __syncthreads();
    if (tid == 0) {
#pragma unroll
        for (int k = 0; k < 4; k++) load_w(sb + OFF_W1 + k * 16384, &tmWh, half * 128, k * 64, sb + M_BAR + (BAR_WH1 + k) * 8);
        load_w(sb + OFF_RX, &tmWe, half * 128, 64, sb + M_BAR + (BAR_W1 + 1) * 8);
    }
    if (tid >= 32 && tid < 32 + NCL) {
        const int c = tid - 32;
        st_rel(&g_flagP[c * NCTA + cta], (tag << 22) | (lds32<M_CO>(sb + c * 4) << 11) | lds32<M_CC>(sb + c * 4));
    }
    TS(2);
    float a0[40], a1[40];
    const uint32_t xH = sb + OFF_RH + nh * 10240;
    sfor<4>([&](auto K) { constexpr int k = K.v;
        mbar_wait(sb + M_BAR + (BAR_H + k) * 8); mbar_wait(sb + M_BAR + (BAR_W2 + k) * 8);
        gemm_chunk<k == 0>(a0, sb + OFF_W0 + k * 16384 + mt * 8192, xH + k * ATOM); });
    TS(3);
    sfor<4>([&](auto K) { constexpr int k = K.v;
        mbar_wait(sb + M_BAR + (BAR_WH1 + k) * 8);
        gemm_chunk<k == 0>(a1, sb + OFF_W1 + k * 16384 + mt * 8192, xH + k * ATOM); });
    wg_wait<4>();
    pin40(a0);
    __syncthreads();
    TS(4);
    if (tid == 0) load_w(sb + OFF_W0 + 49152, &tmWe, half * 128, 0, sb + M_BAR + (BAR_W1 + 0) * 8);
    const uint32_t stOff = ((lane >> 4) * 8 + (lane & 7)) * 128 + (((w * 2 + ((lane >> 3) & 1)) ^ (lane & 7)) << 4);
    const int cr = (tid & 127) >> 3, cc = tid & 7;
    const uint32_t cpOff = cr * 128 + ((cc ^ (cr & 7)) << 4);
    const int rowLim = min(RPC, NN - node0) - nh * 80;
    {
        const uint32_t st = sb + OFF_W0 + wg * 10240;
#pragma unroll
        for (int j = 0; j < 5; j++)
            stsm4t(st + stOff + j * 2048, pack2(0.5f * a0[8 * j], 0.5f * a0[8 * j + 1]), pack2(0.5f * a0[8 * j + 2], 0.5f * a0[8 * j + 3]),
                   pack2(0.5f * a0[8 * j + 4], 0.5f * a0[8 * j + 5]), pack2(0.5f * a0[8 * j + 6], 0.5f * a0[8 * j + 7]));
        bar_wg(wg);
        char* gb = p.B + (size_t)(node0 + nh * 80 + cr) * 512 + half * 256 + mt * 128 + cc * 16;
#pragma unroll
        for (int j = 0; j < 5; j++) { const uint4 v = lds128<0>(st + cpOff + j * 2048); if (cr + 16 * j < rowLim) *(uint4*)(gb + j * 8192) = v; }
    }
    __syncthreads();
    if (tid == 0) {
        load_w(sb + OFF_W0, &tmWe, half * 128, 128, sb + M_BAR + (BAR_W1 + 2) * 8);
        load_w(sb + OFF_W0 + 16384, &tmWe, half * 128, 192, sb + M_BAR + (BAR_W1 + 3) * 8);
    }
    if (tid == 32) st_rel(&g_flagB[cta], tag);
    TS(5);
    mbar_wait(sb + M_BAR + (BAR_W1 + 0) * 8);
    gemm_chunk<true>(a0, sb + OFF_W0 + 49152 + mt * 8192, xH);
    mbar_wait(sb + M_BAR + (BAR_W1 + 1) * 8);
    gemm_chunk<false>(a0, sb + OFF_RX + mt * 8192, xH + ATOM);
    uint32_t runw = 0;
    if (lane < 9 && wid + 16 * lane < NCTA) {
        const uint32_t* f = &g_flagP[cl * NCTA + wid + 16 * lane];
        uint32_t it = 0;
        while (((runw = ld_acq(f)) >> 22) != tag) if (++it > SPIN_LIMIT) break;
        runw &= 0x3fffffu;
    }
    __syncwarp();
    uint32_t mrun[9];
#pragma unroll
    for (int i = 0; i < 9; i++) {
        const uint32_t r = __shfl_sync(~0u, runw, i);
        mrun[i] = (uint32_t)lane < (r & 0x7ffu) ? ldg_cg(&g_meta[(wid + 16 * i) * EPC + (r >> 11) + lane]) : 0xffffffffu;
    }
#pragma unroll
    for (int i = 0; i < 9; i++) if (mrun[i] != 0xffffffffu) reds_inc(sb + M_NC + (mrun[i] >> 23) * 4);
    const bool longRuns = __any_sync(~0u, (runw & 0x7ffu) > 32);
    if (longRuns) {
#pragma unroll 1
        for (int i = 0; i < 9; i++) {
            const uint32_t r = __shfl_sync(~0u, runw, i);
            for (uint32_t k = 32 + lane; k < (r & 0x7ffu); k += 32) reds_inc(sb + M_NC + (ldg_cg(&g_meta[(wid + 16 * i) * EPC + (r >> 11) + k]) >> 23) * 4);
        }
    }
    __syncthreads();
    TS(6);
    if (wid == 0) scan_nodes(sb, lane);
    mbar_wait(sb + M_BAR + (BAR_W1 + 2) * 8);
    gemm_chunk<false>(a0, sb + OFF_W0 + mt * 8192, xH + 2 * ATOM);
    mbar_wait(sb + M_BAR + (BAR_W1 + 3) * 8);
    gemm_chunk<false>(a0, sb + OFF_W0 + 16384 + mt * 8192, xH + 3 * ATOM);
    wg_wait<4>();
    pin40(a1);
    __syncthreads();
    TS(7);
    int ne = lds32<M_NE>(sb);
    const bool multi = ne > RCAP;
    if (!multi) {
#pragma unroll
        for (int i = 0; i < 9; i++) {
            const uint32_t r = __shfl_sync(~0u, runw, i);
            if (mrun[i] != 0xffffffffu) place_one(sb, mrun[i], &g_rec[(wid + 16 * i) * EPC + (r >> 11) + lane]);
        }
        if (longRuns) {
#pragma unroll 1
            for (int i = 0; i < 9; i++) {
                const uint32_t r = __shfl_sync(~0u, runw, i);
                for (uint32_t k = 32 + lane; k < (r & 0x7ffu); k += 32) {
                    const uint32_t ix = (wid + 16 * i) * EPC + (r >> 11) + k;
                    place_one(sb, ldg_cg(&g_meta[ix]), &g_rec[ix]);
                }
            }
        }
        if (tid < 72 && ne + tid < RTOT) { sts128<OFF_W1>(sb + (ne + tid) * 16, 0, 0, 0, 0); sts32<OFF_META>(sb + (ne + tid) * 4, (uint32_t)RPC << 23); }
    }
#pragma unroll
    for (int j = 0; j < 5; j++)
        g_C[(cta * 5 + j) * NTH + tid] = make_uint4(pack2(a1[8 * j], a1[8 * j + 1]), pack2(a1[8 * j + 2], a1[8 * j + 3]),
                                                     pack2(a1[8 * j + 4], a1[8 * j + 5]), pack2(a1[8 * j + 6], a1[8 * j + 7]));
    const int l8 = lane & 7;
    uint32_t wf[5][8], wx[8];
#pragma unroll
    for (int k = 0; k < 5; k++) {
        const int row = k < 4 ? 513 + k : 512;
        const uint4 u = __ldg(p.we + row * 32 + half * 16 + l8), v = __ldg(p.we + row * 32 + half * 16 + 8 + l8);
        wf[k][0] = u.x; wf[k][1] = u.y; wf[k][2] = u.z; wf[k][3] = u.w; wf[k][4] = v.x; wf[k][5] = v.y; wf[k][6] = v.z; wf[k][7] = v.w;
    }
    {
        const uint4 u = __ldg(p.wx + half * 16 + l8), v = __ldg(p.wx + half * 16 + 8 + l8);
        wx[0] = u.x; wx[1] = u.y; wx[2] = u.z; wx[3] = u.w; wx[4] = v.x; wx[5] = v.y; wx[6] = v.z; wx[7] = v.w;
    }
    if (tid < NCL) {
        uint32_t it = 0;
        while (ld_acq(&g_flagB[2 * tid + half]) != tag) if (++it > SPIN_LIMIT) break;
    }
    if (cta == 0 && tid >= 96 && tid < 96 + NCL) {
        uint32_t it = 0;
        while (ld_acq(&g_flagB[2 * (tid - 96) + 1]) != tag) if (++it > SPIN_LIMIT) break;
    }
#pragma unroll
    for (int k = 0; k < 5; k++)
#pragma unroll
        for (int j = 0; j < 8; j++) wf[k][j] = hmul2(wf[k][j], 0x3f003f00u);
    TS(8);
    wg_wait<0>();
    pin40(a0);
    __syncthreads();
    TS(9);
    if (tid == 0) {
        if (cta == 0) g_epoch = tag;
#pragma unroll
        for (int k = 0; k < 4; k++) load_w(sb + OFF_W0 + k * 16384, &tmWh, half * 128, 256 + k * 64, sb + M_BAR + (BAR_WH2 + k) * 8);
    }
    {
        const uint32_t st = sb + mt * PL + nh * 10240;
#pragma unroll
        for (int j = 0; j < 5; j++)
            stsm4t(st + stOff + j * 2048, pack2(0.5f * a0[8 * j], 0.5f * a0[8 * j + 1]), pack2(0.5f * a0[8 * j + 2], 0.5f * a0[8 * j + 3]),
                   pack2(0.5f * a0[8 * j + 4], 0.5f * a0[8 * j + 5]), pack2(0.5f * a0[8 * j + 6], 0.5f * a0[8 * j + 7]));
    }
    float psum = 0.f;
    const int slot = wid * 4 + (lane >> 3);
    const uint64_t Bb = (uint64_t)(p.B + half * 256 + l8 * 16);
    const uint32_t bLo = (uint32_t)Bb, bHi = (uint32_t)(Bb >> 32);
#pragma unroll 1
    for (int round = 0; round < (multi ? NCL : 1); round++) {
        if (multi) {
            __syncthreads();
            for (int i = tid; i < RPC * 16; i += NTH) {
                const uint32_t a = sb + (i >= RPC * 8 ? PL - RPC * 128 : 0) + i * 16;
                if (round == 0) g_Asave[cta * RPC * 16 + i] = lds128<0>(a);
                else { const uint4 v = g_Asave[cta * RPC * 16 + i]; sts128<0>(a, v.x, v.y, v.z, v.w); }
            }
            if (tid < 160) sts32<M_NC>(sb + tid * 4, 0);
            __syncthreads();
            const int pr = 2 * round + (wid & 1);
            const uint32_t r = ((pr ^ wid) & 15) == 0 ? __shfl_sync(~0u, runw, pr >> 4) : 0;
            for (uint32_t k = lane; k < (r & 0x7ffu); k += 32) reds_inc(sb + M_NC + (ldg_cg(&g_meta[pr * EPC + (r >> 11) + k]) >> 23) * 4);
            __syncthreads();
            if (wid == 0) scan_nodes(sb, lane);
            __syncthreads();
            ne = lds32<M_NE>(sb);
            for (uint32_t k = lane; k < (r & 0x7ffu); k += 32) { const uint32_t ix = pr * EPC + (r >> 11) + k; place_one(sb, ldg_cg(&g_meta[ix]), &g_rec[ix]); }
            if (tid < 72) { sts128<OFF_W1>(sb + (ne + tid) * 16, 0, 0, 0, 0); sts32<OFF_META>(sb + (ne + tid) * 4, (uint32_t)RPC << 23); }
        }
        asm volatile("cp.async.wait_all;" ::: "memory");
        __syncthreads();
        TS(10);
        const int L = (ne + NSLOT - 1) / NSLOT;
        uint32_t pr = sb + OFF_W1 + slot * L * 16, po = sb + OFF_META + slot * L * 4;
        const uint32_t pe = po + (L - 1) * 4;
        const uint32_t sideA = sb + (160 + slot) * 128 + (l8 << 4);
        uint32_t A[8], acc[8], px = 0, py = 0, pz = 0, dst = sideA;
#pragma unroll
        for (int j = 0; j < 8; j++) acc[j] = 0;
        if (L > 0) {
            auto rowaddr = [&](uint32_t m) { const uint32_t n = (m >> 23) & 0xff; return sb + n * 128 + ((l8 ^ (n & 7)) << 4); };
            constexpr int D = 2;
            uint4 ring[D][2]; uint32_t mtq[D];
            sfor<D>([&](auto DD) { constexpr int d = DD.v; mtq[d] = lds32<d * 4>(po); const uint32_t lo = mtq[d] * 512 + bLo;
                ring[d][0] = ldg_row<0>(lo, bHi); ring[d][1] = ldg_row<128>(lo, bHi); });
            {
                const uint32_t ra = rowaddr(mtq[0]); const uint4 u = lds128<0>(ra), v = lds128<PL>(ra);
                A[0] = u.x; A[1] = u.y; A[2] = u.z; A[3] = u.w; A[4] = v.x; A[5] = v.y; A[6] = v.z; A[7] = v.w;
                if (slot == 0 || (int32_t)lds32<-4>(po) < 0) dst = ra;
            }
            int s = 0;
            while (true) {
                bool done = false;
                sfor<D>([&](auto DD) { constexpr int d = DD.v;
                    if (!done) {
                        const uint4 f = lds128<d * 16>(pr);
                        const uint32_t mcur = mtq[d]; mtq[d] = lds32<(D + d) * 4>(po);
                        const uint32_t g[8] = {ring[d][0].x, ring[d][0].y, ring[d][0].z, ring[d][0].w, ring[d][1].x, ring[d][1].y, ring[d][1].z, ring[d][1].w};
                        uint32_t x[8];
#pragma unroll
                        for (int j = 0; j < 8; j++) x[j] = hfma2_l(wf[0][j], f.x, g[j]);
                        if (s + d + D < L) { const uint32_t lo = mtq[d] * 512 + bLo; ring[d][0] = ldg_row<0>(lo, bHi); ring[d][1] = ldg_row<128>(lo, bHi); }
                        uint32_t cs = 0;
#pragma unroll
                        for (int j = 0; j < 8; j++) {
                            uint32_t y = hfma2_h(wf[1][j], f.x, x[j]); y = hfma2_l(wf[2][j], f.y, y); y = hfma2_h(wf[3][j], f.y, y);
                            y = hfma2_l(wf[4][j], f.z, y); y = hadd2(y, A[j]);
                            const uint32_t m = hfma2(y, tanh2(y), y);
                            acc[j] = hadd2(acc[j], m);
                            cs = j == 0 ? hmul2(m, wx[j]) : hfma2(m, wx[j], cs);
                        }
                        px = hfma2_h(cs, f.z, px); py = hfma2_l(cs, f.w, py); pz = hfma2_h(cs, f.w, pz);
                        if ((int32_t)mcur < 0) {
                            sts128<0>(dst, acc[0], acc[1], acc[2], acc[3]); sts128<PL>(dst, acc[4], acc[5], acc[6], acc[7]); sts128<2 * PL>(dst, px, py, pz, pz);
                            dst = rowaddr(mtq[(d + 1) % D]);
                            const uint4 u = lds128<0>(dst), v = lds128<PL>(dst);
                            A[0] = u.x; A[1] = u.y; A[2] = u.z; A[3] = u.w; A[4] = v.x; A[5] = v.y; A[6] = v.z; A[7] = v.w;
#pragma unroll
                            for (int j = 0; j < 8; j++) acc[j] = 0;
                            px = py = pz = 0;
                        }
                        done = s + d + 1 >= L;
                    } });
                if (done) break;
                s += D; pr += D * 16; po += D * 4;
            }
        }
        TS(11);
        const uint32_t mlast = L > 0 ? lds32<0>(pe) : 0x80000000u;
        const bool pend = (int32_t)mlast >= 0 && (mlast >> 23) != RPC;
        if (pend && dst == sideA) { sts128<0>(dst, acc[0], acc[1], acc[2], acc[3]); sts128<PL>(dst, acc[4], acc[5], acc[6], acc[7]); sts128<2 * PL>(dst, px, py, pz, pz); }
        __syncthreads();
        if (pend && dst != sideA) {
            float fa[22];
#pragma unroll
            for (int j = 0; j < 8; j++) { fa[2 * j] = blo(acc[j]); fa[2 * j + 1] = bhi(acc[j]); }
            fa[16] = blo(px); fa[17] = bhi(px); fa[18] = blo(py); fa[19] = bhi(py); fa[20] = blo(pz); fa[21] = bhi(pz);
            for (int t = 1; t < NSLOT - slot; t++) {
                const uint4 b0 = lds128<0>(sideA + t * 128), b1 = lds128<PL>(sideA + t * 128), b2 = lds128<2 * PL>(sideA + t * 128);
                const uint32_t b[11] = {b0.x, b0.y, b0.z, b0.w, b1.x, b1.y, b1.z, b1.w, b2.x, b2.y, b2.z};
#pragma unroll
                for (int j = 0; j < 11; j++) { fa[2 * j] += blo(b[j]); fa[2 * j + 1] += bhi(b[j]); }
                if ((lds32<0>(pe + t * L * 4) >> 23) != (mlast >> 23)) break;
            }
            sts128<0>(dst, pack2(fa[0], fa[1]), pack2(fa[2], fa[3]), pack2(fa[4], fa[5]), pack2(fa[6], fa[7]));
            sts128<PL>(dst, pack2(fa[8], fa[9]), pack2(fa[10], fa[11]), pack2(fa[12], fa[13]), pack2(fa[14], fa[15]));
            sts128<2 * PL>(dst, pack2(fa[16], fa[17]), pack2(fa[18], fa[19]), pack2(fa[20], fa[21]), 0);
        }
#pragma unroll
        for (int i = 0; i < 3; i++) {
            const int n = slot + i * NSLOT;
            if (n < RPC && lds32<M_NC>(sb + n * 4) == 0) { const uint32_t a = sb + n * 128 + (l8 << 4); sts128<0>(a, 0, 0, 0, 0); sts128<PL>(a, 0, 0, 0, 0); sts128<2 * PL>(a, 0, 0, 0, 0); }
        }
        if (multi) {
            __syncthreads();
            for (int i = tid; i < RPC * 64; i += NTH) {
                const uint32_t a = sb + (i >= RPC * 32 ? PL - RPC * 128 : 0) + i * 4;
                float2* g = (float2*)g_macc + cta * RPC * 64 + i;
                float2 v = round == 0 ? make_float2(0.f, 0.f) : *g;
                const uint32_t m = lds32<0>(a); v.x += blo(m); v.y += bhi(m);
                *g = v;
                if (round == NCL - 1) sts32<0>(a, pack2(v.x, v.y));
            }
            if (round < NCL - 1 && tid < RPC * 3) {
                const uint32_t a = sb + 2 * PL + (tid / 3) * 128 + (tid % 3) * 4;
#pragma unroll
                for (int l = 0; l < 8; l++) { const uint32_t v = lds32<0>(a + l * 16); psum += blo(v) + bhi(v); }
            }
        }
    }
    uint4 cv[5], hv[5];
    const size_t go = (size_t)(node0 + nh * 80 + cr) * 32 + half * 16 + mt * 8 + cc;
#pragma unroll
    for (int j = 0; j < 5; j++) { cv[j] = g_C[(cta * 5 + j) * NTH + tid]; hv[j] = cr + 16 * j < rowLim ? __ldg(p.h + go + j * 512) : make_uint4(0, 0, 0, 0); }
    fence_async();
    asm volatile("barrier.cluster.arrive.aligned;\nbarrier.cluster.wait.aligned;" ::: "memory");
    TS(12);
    uint32_t peer; asm("mapa.shared::cluster.u32 %0,%1,%2;" : "=r"(peer) : "r"(sb), "r"(half ^ 1));
    if (tid == 0) {
#pragma unroll
        for (int k = 0; k < 2; k++)
            asm volatile("cp.async.bulk.shared::cluster.shared::cta.mbarrier::complete_tx::bytes [%0],[%1],%2,[%3];"
                         ::"r"(peer + OFF_W1 + k * ATOM), "r"(sb + k * PL), "n"(ATOM), "r"(peer + M_BAR + BAR_M * 8) : "memory");
    }
#pragma unroll
    for (int j = 0; j < 5; j++) {
        a0[8 * j] = blo(cv[j].x); a0[8 * j + 1] = bhi(cv[j].x); a0[8 * j + 2] = blo(cv[j].y); a0[8 * j + 3] = bhi(cv[j].y);
        a0[8 * j + 4] = blo(cv[j].z); a0[8 * j + 5] = bhi(cv[j].z); a0[8 * j + 6] = blo(cv[j].w); a0[8 * j + 7] = bhi(cv[j].w);
    }
    pin40(a0);
#pragma unroll
    for (int k = 0; k < 4; k++) mbar_wait(sb + M_BAR + (BAR_WH2 + k) * 8);
    gemm_chunk<false>(a0, sb + OFF_W0 + (half * 2) * 16384 + mt * 8192, sb + nh * 10240);
    gemm_chunk<false>(a0, sb + OFF_W0 + (half * 2 + 1) * 16384 + mt * 8192, sb + PL + nh * 10240);
    if (tid < RPC * 3) {
        const uint32_t a = sb + 2 * PL + (tid / 3) * 128 + (tid % 3) * 4;
#pragma unroll
        for (int l = 0; l < 8; l++) { const uint32_t v = lds32<0>(a + l * 16); psum += blo(v) + bhi(v); }
        if (half == 1) asm volatile("st.shared::cluster.f32 [%0],%1;" ::"r"(peer + OFF_PP + tid * 4), "f"(psum) : "memory");
    }
    mbar_wait(sb + M_BAR + BAR_M * 8);
    asm volatile("barrier.cluster.arrive.aligned;" ::: "memory");
    gemm_chunk<false>(a0, sb + OFF_W0 + (2 - half * 2) * 16384 + mt * 8192, sb + OFF_W1 + nh * 10240);
    gemm_chunk<false>(a0, sb + OFF_W0 + (3 - half * 2) * 16384 + mt * 8192, sb + OFF_W1 + ATOM + nh * 10240);
    wg_wait<0>();
    pin40(a0);
    TS(13);
    {
        const uint32_t st = sb + (nh == 0 ? OFF_W1 + 2 * ATOM : 2 * PL + 160 * 128) + mt * 10240;
#pragma unroll
        for (int i = 0; i < 40; i++) { const float y = 0.5f * a0[i]; a0[i] = fmaf(y, tanh1(y), y); }
#pragma unroll
        for (int j = 0; j < 5; j++)
            stsm4t(st + stOff + j * 2048, pack2(a0[8 * j], a0[8 * j + 1]), pack2(a0[8 * j + 2], a0[8 * j + 3]),
                   pack2(a0[8 * j + 4], a0[8 * j + 5]), pack2(a0[8 * j + 6], a0[8 * j + 7]));
        bar_wg(wg);
#pragma unroll
        for (int j = 0; j < 5; j++) {
            const uint4 v = lds128<0>(st + cpOff + j * 2048);
            if (cr + 16 * j < rowLim) p.out_h[go + j * 512] = make_uint4(hadd2(hv[j].x, v.x), hadd2(hv[j].y, v.y), hadd2(hv[j].z, v.z), hadd2(hv[j].w, v.w));
        }
    }
    asm volatile("barrier.cluster.wait.aligned;" ::: "memory");
    if (half == 0 && tid < RPC * 3 && node0 * 3 + tid < NN * 3) {
        const float v = psum + __uint_as_float(lds32<OFF_PP>(sb + tid * 4)) + blo(p.pos[node0 * 3 + tid]);
        p.out_pos[node0 * 3 + tid] = (unsigned short)pack2(v, 0.f);
    }
    TS(14);
}

typedef CUresult (*EncodeFn)(CUtensorMap*, CUtensorMapDataType, cuuint32_t, void*, const cuuint64_t*, const cuuint64_t*,
                             const cuuint32_t*, const cuuint32_t*, CUtensorMapInterleave, CUtensorMapSwizzle,
                             CUtensorMapL2promotion, CUtensorMapFloatOOBfill);

void make_map(EncodeFn fn, CUtensorMap* m, void* ptr, uint64_t rows, uint32_t boxRows) {
    const cuuint64_t dims[2] = {256, rows}, strides[1] = {512};
    const cuuint32_t box[2] = {64, boxRows}, es[2] = {1, 1};
    fn(m, CU_TENSOR_MAP_DATA_TYPE_BFLOAT16, 2, ptr, dims, strides, box, es, CU_TENSOR_MAP_INTERLEAVE_NONE,
       CU_TENSOR_MAP_SWIZZLE_128B, CU_TENSOR_MAP_L2_PROMOTION_L2_256B, CU_TENSOR_MAP_FLOAT_OOB_FILL_NONE);
}

}

extern "C" void kernel_launch(void* const* d_in, const int* in_sizes, int n_in, void* d_out, int out_size) {
    static EncodeFn enc = nullptr;
    static char* bptr = nullptr;
    if (!enc) {
        void* f = nullptr; cudaDriverEntryPointQueryResult q;
        cudaGetDriverEntryPoint("cuTensorMapEncodeTiled", &f, cudaEnableDefault, &q);
        enc = (EncodeFn)f;
        cudaFuncSetAttribute(egnn_kernel, cudaFuncAttributeMaxDynamicSharedMemorySize, SMEM_TOTAL);
        void* b = nullptr; cudaGetSymbolAddress(&b, g_B);
        bptr = (char*)b;
        if (((uint64_t)bptr >> 32) != (((uint64_t)bptr + (size_t)NN * 512 - 1) >> 32)) bptr += (size_t)NN * 512;
    }
    CUtensorMap tmH, tmWe, tmWh;
    make_map(enc, &tmH, d_in[0], NN, RPC);
    make_map(enc, &tmWe, d_in[5], 517, 64);
    make_map(enc, &tmWh, d_in[7], 512, 64);
    Params p;
    p.h = (const uint4*)d_in[0]; p.pos = (const unsigned short*)d_in[1]; p.ea = (const uint2*)d_in[2];
    p.src = (const int*)d_in[3]; p.dst = (const int*)d_in[4]; p.we = (const uint4*)d_in[5]; p.wx = (const uint4*)d_in[6];
    p.out_h = (uint4*)d_out; p.out_pos = (unsigned short*)d_out + (size_t)NN * 256; p.B = bptr;
    egnn_kernel<<<NCTA, NTH, SMEM_TOTAL, cudaStreamPerThread>>>(tmH, tmWe, tmWh, p);
}
```

```cpp
#include <cuda_runtime.h>
#include <cuda_bf16.h>
#include <cuda.h>
#include <stdint.h>

namespace {

constexpr int NN = 10000, NE = 160000, NCL = 66, RPC = 152, NCTA = 132, EPC = 1216, NTH = 512;
constexpr int NSLOT = 64, RCAP = 3136, ECAP = 2880, RTOT = ECAP + 32;
constexpr int OFF_RX = 0, OFF_RH = 20480, OFF_WQ = 98304, OFF_WR = 163840, OFF_MISC = 229376, SMEM_TOTAL = 232448;
constexpr int ATOM = RPC * 128;
constexpr int PL = 216 * 128;
constexpr int OFF_STM = OFF_WQ + 60416;
constexpr int OFF_P = 2 * PL;
constexpr int OFF_PP = OFF_P + RPC * 64;
constexpr int OFF_C = OFF_P + 14336;
constexpr int OFF_MP = OFF_C + 2 * ATOM;
constexpr int OFF_WF = OFF_MP + 2 * ATOM;
constexpr int OFF_META = OFF_WF + 16384 + 4;
constexpr int OFF_IDX = OFF_META + RTOT * 4;
constexpr int OFF_REC = (OFF_IDX + RTOT * 2 + 127) / 128 * 128;
constexpr int ZREC = (ECAP + 56) * 16, OFF_ZERO = OFF_REC + ZREC;
static_assert(OFF_ZERO + 48 <= OFF_MISC && OFF_META - 4 >= OFF_WR && OFF_C % 1024 == 0 && OFF_WF + 65536 <= OFF_MISC, "smem map");
constexpr int M_BAR = OFF_MISC;
constexpr int M_CC = OFF_MISC + 272;
constexpr int M_CO = OFF_MISC + 576;
constexpr int M_NC = OFF_MISC + 896;
constexpr int M_SE = OFF_MISC + 1664;
constexpr int M_GD = OFF_MISC + 2432;
constexpr int M_NE = OFF_MISC + 2816, M_NL = OFF_MISC + 2832;
#define HV 33
#define TV 5
#define LD 1
#define EV 17
constexpr int BAR_H = 0, BAR_W2 = 4, BAR_WH1 = 8, BAR_W1 = 12, BAR_WH2 = 16, BAR_POS = 20, BAR_M = 21, BAR_PP = 22, BAR_RDY = 23,
              BAR_B = 24, BAR_BS = 25, BAR_REC = 26, BAR_E = 27, BAR_O = 28, NBAR = 32;
constexpr int NPT = 480, EPT = 3;
constexpr int NSW = 7, NST = NSW * 32, IPT = RCAP / NST, SUB = IPT * 32;
constexpr uint32_t SPIN_LIMIT = 1u << 20;

__device__ __align__(1024) uint4 g_B[2 * NCL * RPC * 32];
__device__ __align__(128) uint4 g_rec[NCL * RCAP];
__device__ __align__(128) uint32_t g_meta[NCL * RCAP];
__device__ __align__(128) uint32_t g_cur[NSW * NCL * 8];
__device__ __align__(128) unsigned long long g_cnt[48];
#define TS(i)
#define TSX(i, t)

struct Params {
    const int* dst; const int* src; const uint2* ea; const unsigned short* pos; uint32_t* cur; unsigned long long* cnt;
    uint4* rec; uint32_t* meta; const uint4* we; const uint4* wx; const uint4* wh; const uint4* h; char* B; uint4* out_h;
};

__device__ __forceinline__ uint32_t hfma2(uint32_t a, uint32_t b, uint32_t c) { uint32_t r; asm("fma.rn.bf16x2 %0,%1,%2,%3;" : "=r"(r) : "r"(a), "r"(b), "r"(c)); return r; }
__device__ __forceinline__ uint32_t hmul2(uint32_t a, uint32_t b) { uint32_t r; asm("mul.rn.bf16x2 %0,%1,%2;" : "=r"(r) : "r"(a), "r"(b)); return r; }
__device__ __forceinline__ uint32_t hadd2(uint32_t a, uint32_t b) { uint32_t r; asm("add.rn.bf16x2 %0,%1,%2;" : "=r"(r) : "r"(a), "r"(b)); return r; }
__device__ __forceinline__ uint32_t hsub2(uint32_t a, uint32_t b) { uint32_t r; asm("sub.rn.bf16x2 %0,%1,%2;" : "=r"(r) : "r"(a), "r"(b)); return r; }
__device__ __forceinline__ uint32_t hfma2_l(uint32_t a, uint32_t b, uint32_t c) { uint32_t r; asm("{.reg .b16 l,h; .reg .b32 t; mov.b32 {l,h},%2; mov.b32 t,{l,l}; fma.rn.bf16x2 %0,%1,t,%3;}" : "=r"(r) : "r"(a), "r"(b), "r"(c)); return r; }
__device__ __forceinline__ uint32_t hfma2_lv(uint32_t a, uint32_t b, uint32_t c) { uint32_t r; asm volatile("{.reg .b16 l,h; .reg .b32 t; mov.b32 {l,h},%2; mov.b32 t,{l,l}; fma.rn.bf16x2 %0,%1,t,%3;}" : "=r"(r) : "r"(a), "r"(b), "r"(c)); return r; }
__device__ __forceinline__ uint32_t hfma2_h(uint32_t a, uint32_t b, uint32_t c) { uint32_t r; asm("{.reg .b16 l,h; .reg .b32 t; mov.b32 {l,h},%2; mov.b32 t,{h,h}; fma.rn.bf16x2 %0,%1,t,%3;}" : "=r"(r) : "r"(a), "r"(b), "r"(c)); return r; }
__device__ __forceinline__ uint32_t hsum2(uint32_t a) { uint32_t r; asm("{.reg .b16 l,h; .reg .b32 x,y; mov.b32 {l,h},%1; mov.b32 x,{l,l}; mov.b32 y,{h,h}; add.rn.bf16x2 %0,x,y;}" : "=r"(r) : "r"(a)); return r; }
__device__ __forceinline__ uint32_t tanh2(uint32_t a) { uint32_t r; asm("tanh.approx.bf16x2 %0,%1;" : "=r"(r) : "r"(a)); return r; }
__device__ __forceinline__ float tanh1(float x) { float r; asm("tanh.approx.f32 %0,%1;" : "=f"(r) : "f"(x)); return r; }
__device__ __forceinline__ uint32_t pack2(float lo, float hi) { uint32_t r; asm("cvt.rn.bf16x2.f32 %0,%1,%2;" : "=r"(r) : "f"(hi), "f"(lo)); return r; }
__device__ __forceinline__ float blo(uint32_t v) { return __uint_as_float(v << 16); }
__device__ __forceinline__ float bhi(uint32_t v) { return __uint_as_float(v & 0xffff0000u); }
template <int OFF> __device__ __forceinline__ uint4 ldg_row(uint32_t lo, uint32_t hi) {
    uint4 v; asm volatile("{.reg .b64 a; mov.b64 a,{%4,%5}; ld.global.L1::no_allocate.v4.u32 {%0,%1,%2,%3},[a+%6];}"
                          : "=r"(v.x), "=r"(v.y), "=r"(v.z), "=r"(v.w) : "r"(lo), "r"(hi), "n"(OFF)); return v; }
template <int OFF> __device__ __forceinline__ uint4 lds128(uint32_t a) { uint4 v; asm volatile("ld.shared.v4.u32 {%0,%1,%2,%3},[%4+%5];" : "=r"(v.x), "=r"(v.y), "=r"(v.z), "=r"(v.w) : "r"(a), "n"(OFF)); return v; }
template <int OFF> __device__ __forceinline__ uint32_t lds32(uint32_t a) { uint32_t v; asm volatile("ld.shared.u32 %0,[%1+%2];" : "=r"(v) : "r"(a), "n"(OFF)); return v; }
template <int OFF> __device__ __forceinline__ uint32_t lds16(uint32_t a) { uint32_t v; asm volatile("ld.shared.u16 %0,[%1+%2];" : "=r"(v) : "r"(a), "n"(OFF)); return v; }
template <int OFF> __device__ __forceinline__ void sts128(uint32_t a, uint32_t x, uint32_t y, uint32_t z, uint32_t w) { asm volatile("st.volatile.shared.v4.u32 [%0+%5],{%1,%2,%3,%4};" ::"r"(a), "r"(x), "r"(y), "r"(z), "r"(w), "n"(OFF) : "memory"); }
template <int OFF> __device__ __forceinline__ void sts32(uint32_t a, uint32_t x) { asm volatile("st.shared.u32 [%0+%2],%1;" ::"r"(a), "r"(x), "n"(OFF) : "memory"); }
template <int OFF> __device__ __forceinline__ void sts64(uint32_t a, uint32_t x, uint32_t y) { asm volatile("st.volatile.shared.v2.u32 [%0+%3],{%1,%2};" ::"r"(a), "r"(x), "r"(y), "n"(OFF) : "memory"); }
template <int OFF> __device__ __forceinline__ uint2 lds64(uint32_t a) { uint2 v; asm volatile("ld.shared.v2.u32 {%0,%1},[%2+%3];" : "=r"(v.x), "=r"(v.y) : "r"(a), "n"(OFF)); return v; }
template <int OFF> __device__ __forceinline__ void sts16(uint32_t a, uint32_t x) { asm volatile("st.shared.u16 [%0+%2],%1;" ::"r"(a), "h"((unsigned short)x), "n"(OFF) : "memory"); }
__device__ __forceinline__ uint32_t atoms_inc(uint32_t a) { uint32_t r; asm volatile("atom.shared.add.u32 %0,[%1],1;" : "=r"(r) : "r"(a) : "memory"); return r; }
__device__ __forceinline__ void reds_inc(uint32_t a) { asm volatile("red.shared.add.u32 [%0],1;" ::"r"(a) : "memory"); }
__device__ __forceinline__ uint32_t ld_acq(const uint32_t* p) { uint32_t v; asm volatile("ld.acquire.gpu.global.u32 %0,[%1];" : "=r"(v) : "l"(p) : "memory"); return v; }
__device__ __forceinline__ void st_rel(uint32_t* p, uint32_t v) { asm volatile("st.release.gpu.global.u32 [%0],%1;" ::"l"(p), "r"(v) : "memory"); }
__device__ __forceinline__ uint32_t ld_rlx(const uint32_t* p) { uint32_t v; asm volatile("ld.relaxed.gpu.global.u32 %0,[%1];" : "=r"(v) : "l"(p) : "memory"); return v; }
__device__ __forceinline__ void st_rlx(uint32_t* p, uint32_t v) { asm volatile("st.relaxed.gpu.global.u32 [%0],%1;" ::"l"(p), "r"(v) : "memory"); }
__device__ __forceinline__ uint32_t ldg_cg(const uint32_t* p) { uint32_t v; asm volatile("ld.global.cg.u32 %0,[%1];" : "=r"(v) : "l"(p) : "memory"); return v; }
__device__ __forceinline__ void mbar_init(uint32_t bar, uint32_t cnt) { asm volatile("mbarrier.init.shared::cta.b64 [%0],%1;" ::"r"(bar), "r"(cnt) : "memory"); }
__device__ __forceinline__ void mbar_expect(uint32_t bar, uint32_t bytes) { asm volatile("mbarrier.arrive.expect_tx.shared::cta.b64 _,[%0],%1;" ::"r"(bar), "r"(bytes) : "memory"); }
__device__ __forceinline__ void mbar_wait(uint32_t bar) {
    asm volatile("{.reg .pred p; .reg .u32 c; mov.u32 c,0;\n"
                 "LW: mbarrier.try_wait.parity.shared::cta.b64 p,[%0],0; @p bra LD; add.u32 c,c,1; setp.lt.u32 p,c,%1; @p bra LW;\n"
                 "LD: }" ::"r"(bar), "n"(SPIN_LIMIT) : "memory");
}
__device__ __forceinline__ void tma2d(uint32_t dst, const CUtensorMap* m, int c0, int c1, uint32_t bar) {
    asm volatile("cp.async.bulk.tensor.2d.shared::cluster.global.mbarrier::complete_tx::bytes [%0],[%1,{%3,%4}],[%2];"
                 ::"r"(dst), "l"((uint64_t)m), "r"(bar), "r"(c0), "r"(c1) : "memory");
}
__device__ __forceinline__ void load_w(uint32_t dst, uint32_t ms, const CUtensorMap* m, int col, int row, uint32_t bar) {
    mbar_expect(bar, 16384); tma2d(dst, m, col, row, bar); tma2d(dst + ms, m, col + 64, row, bar);
}
__device__ __forceinline__ void mbar_arrive(uint32_t bar) { asm volatile("mbarrier.arrive.shared::cta.b64 _,[%0];" ::"r"(bar) : "memory"); }
__device__ __forceinline__ void prefetch_l2(const void* p) { asm volatile("prefetch.global.L2 [%0];" ::"l"(p)); }
__device__ __forceinline__ void fence_async() { asm volatile("fence.proxy.async.shared::cta;" ::: "memory"); }
__device__ __forceinline__ void bar_wg(int wg) { asm volatile("bar.sync %0,128;" ::"r"(wg + 1) : "memory"); }
__device__ __forceinline__ void wg_fence() { asm volatile("wgmma.fence.sync.aligned;" ::: "memory"); }
__device__ __forceinline__ void wg_commit() { asm volatile("wgmma.commit_group.sync.aligned;" ::: "memory"); }
template <int N_> __device__ __forceinline__ void wg_wait() { asm volatile("wgmma.wait_group.sync.aligned %0;" ::"n"(N_) : "memory"); }
#define R8(o) "+f"(d[o]), "+f"(d[o + 1]), "+f"(d[o + 2]), "+f"(d[o + 3]), "+f"(d[o + 4]), "+f"(d[o + 5]), "+f"(d[o + 6]), "+f"(d[o + 7])
template <int SC, int OA, int OB> __device__ __forceinline__ void wgmma152(float* d, uint32_t a, uint32_t b) {
    asm volatile("{.reg .b64 da, db; .reg .b32 x, y; add.u32 x,%76,%79; add.u32 y,%77,%80; mov.b64 da,{x,0x40000040}; mov.b64 db,{y,0x40000040};\n"
                 "wgmma.mma_async.sync.aligned.m64n152k16.f32.bf16.bf16 {%0,%1,%2,%3,%4,%5,%6,%7,%8,%9,%10,%11,%12,%13,%14,%15,%16,%17,%18,%19,%20,%21,%22,%23,%24,%25,%26,%27,%28,%29,%30,%31,%32,%33,%34,%35,%36,%37,%38,%39,%40,%41,%42,%43,%44,%45,%46,%47,%48,%49,%50,%51,%52,%53,%54,%55,%56,%57,%58,%59,%60,%61,%62,%63,%64,%65,%66,%67,%68,%69,%70,%71,%72,%73,%74,%75},da,db,%78,1,1,1,0;}"
                 : R8(0), R8(8), R8(16), R8(24), R8(32), R8(40), R8(48), R8(56), R8(64), "+f"(d[72]), "+f"(d[73]), "+f"(d[74]), "+f"(d[75]) : "r"(a), "r"(b), "n"(SC), "n"(OA), "n"(OB));
}
template <bool FIRST, int OW, int OX> __device__ __forceinline__ void gemm_chunk(float* d, uint32_t wd, uint32_t xd) {
    wg_fence();
    wgmma152<FIRST ? 0 : 1, OW / 16, OX / 16>(d, wd, xd);
    wgmma152<1, OW / 16 + 128, OX / 16 + 2>(d, wd, xd); wgmma152<1, OW / 16 + 256, OX / 16 + 4>(d, wd, xd); wgmma152<1, OW / 16 + 384, OX / 16 + 6>(d, wd, xd);
    wg_commit();
}
template <int N_> __device__ __forceinline__ void pin(float* d) {
#pragma unroll
    for (int i = 0; i < N_; i++) asm volatile("" : "+f"(d[i])::"memory");
}
__device__ __forceinline__ void stsm2t(uint32_t a, uint32_t x, uint32_t y) {
    asm volatile("stmatrix.sync.aligned.m8n8.x2.trans.shared.b16 [%0],{%1,%2};" ::"r"(a), "r"(x), "r"(y) : "memory");
}
__device__ __forceinline__ void stsm4t(uint32_t a, uint32_t x, uint32_t y, uint32_t z, uint32_t w) {
    asm volatile("stmatrix.sync.aligned.m8n8.x4.trans.shared.b16 [%0],{%1,%2,%3,%4};" ::"r"(a), "r"(x), "r"(y), "r"(z), "r"(w) : "memory");
}
template <int I> struct IC { static constexpr int v = I; };
template <int N_, class F> __device__ __forceinline__ void sfor(F f) { if constexpr (N_ > 0) { sfor<N_ - 1>(f); f(IC<N_ - 1>{}); } }

__device__ __forceinline__ void scan_nodes(uint32_t sb, int lane) {
    uint32_t c[5], s = 0;
#pragma unroll
    for (int i = 0; i < 5; i++) { c[i] = lds32<M_NC>(sb + (lane * 5 + i) * 4); s += c[i]; }
    uint32_t x = s;
#pragma unroll
    for (int o = 1; o < 32; o <<= 1) { uint32_t y = __shfl_up_sync(~0u, x, o); if (lane >= o) x += y; }
    uint32_t b = x - s;
#pragma unroll
    for (int i = 0; i < 5; i++) { sts32<M_SE>(sb + (lane * 5 + i) * 4, b | ((b + c[i]) << 16)); b += c[i]; }
    if (lane == 31) sts32<M_NE>(sb, x);
}
__device__ __forceinline__ void scan_clusters(uint32_t sb, int lane) {
    uint32_t c[3], s = 0;
#pragma unroll
    for (int i = 0; i < 3; i++) { c[i] = lane < 22 ? lds32<M_CC>(sb + (lane * 3 + i) * 4) : 0; s += c[i]; }
    uint32_t x = s;
#pragma unroll
    for (int o = 1; o < 32; o <<= 1) { uint32_t y = __shfl_up_sync(~0u, x, o); if (lane >= o) x += y; }
    uint32_t b = x - s;
#pragma unroll
    for (int i = 0; i < 3; i++) { if (lane < 22) sts32<M_CO>(sb + (lane * 3 + i) * 4, b); b += c[i]; }
    __syncwarp();
}
__device__ __forceinline__ uint2 geom(uint32_t dx0, uint32_t dyz0, uint32_t sx, uint32_t syz) {
    const uint32_t dx = hsub2(dx0, sx), dyz = hsub2(dyz0, syz), qx = hmul2(dx, dx), qyz = hmul2(dyz, dyz);
    return make_uint2(__byte_perm(pack2((blo(qx) + blo(qyz)) + bhi(qyz), 0.f), dx, 0x5410), dyz);
}
template <int OFF> __device__ __forceinline__ void send16(uint32_t peer, uint32_t off, uint32_t x, uint32_t y, uint32_t z, uint32_t w) {
    asm volatile("{.reg .pred p; setp.lt.u32 p,%7,%8; @p st.async.weak.shared::cluster.mbarrier::complete_tx::bytes.v4.b32 [%0+%6],{%1,%2,%3,%4},[%5];}"
                 ::"r"(peer + off), "r"(x), "r"(y), "r"(z), "r"(w), "r"(peer + M_BAR + BAR_M * 8), "n"(OFF_MP + OFF), "r"(off), "n"(RPC * 128) : "memory");
}
__device__ __forceinline__ void pad_records(uint32_t sb, int ne, int t) {
    if (t < 72 && ne + t < RTOT - 16) { sts16<OFF_IDX>(sb + (ne + t) * 2, ZREC); sts32<OFF_META>(sb + (ne + t) * 4, RPC); }
    if (t >= 72 && t < 75) { sts128<OFF_ZERO - 72 * 16>(sb + t * 16, 0, 0, 0, 0); sts32<OFF_META - 4>(sb, 0xff); }
}

__global__ void __cluster_dims__(2, 1, 1) __launch_bounds__(NTH, 1)
egnn_kernel(const Params p, const __grid_constant__ CUtensorMap tmH, const __grid_constant__ CUtensorMap tmWe,
            const __grid_constant__ CUtensorMap tmWh, const __grid_constant__ CUtensorMap tmB) {
    extern __shared__ __align__(1024) unsigned char smem[];
    const uint32_t sb = (uint32_t)__cvta_generic_to_shared(smem);
    const int tid = threadIdx.x, lane = tid & 31;
    const int cta = blockIdx.x, cl = cta >> 1, half = cta & 1, node0 = cl * RPC;
    const uint32_t bars = sb + M_BAR;
    uint32_t peer; asm("mapa.shared::cluster.u32 %0,%1,%2;" : "=r"(peer) : "r"(sb), "r"(half ^ 1));
    const int l8 = lane & 7;
    uint32_t wf[5][8], wx[8];
    auto load_edge_weights = [&]() {
#pragma unroll
        for (int k = 0; k < 6; k++) {
            const uint4* q = (k < 4 ? p.we + (513 + k) * 32 : k == 4 ? p.we + 512 * 32 : p.wx) + half * 16 + l8;
            uint32_t* o = k < 5 ? wf[k] : wx;
            asm volatile("ld.global.u32 %0,[%8]; ld.global.u32 %1,[%8+4]; ld.global.u32 %2,[%8+8]; ld.global.u32 %3,[%8+12];"
                         "ld.global.u32 %4,[%8+128]; ld.global.u32 %5,[%8+132]; ld.global.u32 %6,[%8+136]; ld.global.u32 %7,[%8+140];"
                         : "=r"(o[0]), "=r"(o[1]), "=r"(o[2]), "=r"(o[3]), "=r"(o[4]), "=r"(o[5]), "=r"(o[6]), "=r"(o[7]) : "l"(q));
        }
    };
    const int kx = (HV & 16) ? half * 2 : 0;
    auto load_hw = [&]() {
#pragma unroll
        for (int k = 0; k < 4; k++) {
            mbar_expect(bars + (BAR_H + k) * 8, ATOM); tma2d(sb + OFF_RH + k * ATOM, &tmH, (k ^ kx) * 64, node0, bars + (BAR_H + k) * 8);
            load_w(sb + OFF_WR + k * 8192, 32768, &tmWe, half * 128, 256 + (k ^ kx) * 64, bars + (BAR_W2 + k) * 8);
        }
    };
    auto load_wf = [&](int k) {
        const int row = 256 + (half ^ (k & 1)) * 128;
        mbar_expect(bars + (BAR_WH2 + k) * 8, 16384);
        tma2d(sb + OFF_WF + k * 16384, &tmWh, half * 128 + (k >> 1) * 64, row, bars + (BAR_WH2 + k) * 8);
        tma2d(sb + OFF_WF + k * 16384 + 8192, &tmWh, half * 128 + (k >> 1) * 64, row + 64, bars + (BAR_WH2 + k) * 8);
    };
    auto copy_out = [&](auto NI_, auto NT_, int t) {
        constexpr int NI = NI_.v, NT = NT_.v;
        const int nloc = min(EPC, NE - cta * EPC);
        uint32_t cm[NI], cq[NI]; uint4 cv[NI];
#pragma unroll
        for (int i = 0; i < NI; i++) { const int l = min(t + i * NT, nloc - 1); cm[i] = lds32<OFF_STM>(sb + l * 4); cv[i] = lds128<OFF_RX>(sb + l * 16); }
#pragma unroll
        for (int i = 0; i < NI; i++) { cq[i] = (t + i * NT + lds32<M_GD>(sb + ((cm[i] >> 6) & 0x1fc))) & 0xffffffu; if (t + i * NT >= nloc) cq[i] = SUB; }
#pragma unroll
        for (int i = 0; i < NI; i++) {
            const uint32_t g = ((cm[i] >> 8) & 0x7f) * RCAP + (cta % NSW) * SUB + cq[i];
            asm volatile("{.reg .pred p; setp.lt.u32 p,%7,%8; @p st.global.v4.u32 [%0],{%2,%3,%4,%5}; @p st.global.u32 [%1],%6;}"
                         ::"l"(p.rec + g), "l"(p.meta + g), "r"(cv[i].x), "r"(cv[i].y), "r"(cv[i].z), "r"(cv[i].w), "r"(cm[i] & 0xfffc00ffu), "r"(cq[i]), "n"(SUB) : "memory");
        }
    };
    TS(0);
    if (tid == 480) {
        mbar_init(bars + BAR_POS * 8, 1);
        asm volatile("fence.mbarrier_init.release.cluster;" ::: "memory");
        mbar_expect(bars + BAR_POS * 8, NN * 6);
        asm volatile("cp.async.bulk.shared::cluster.global.mbarrier::complete_tx::bytes [%0],[%1],%2,[%3];"
                     ::"r"(sb + OFF_WQ), "l"(p.pos), "n"(NN * 6), "r"(bars + BAR_POS * 8) : "memory");
        TSX(30, 480);
    }
    if (tid >= NPT) { __syncwarp(); asm volatile("bar.arrive 9,512;" ::: "memory"); }
    unsigned long long epoch = 0;
    uint32_t cbase;
    if (tid < NPT) {
        int es[EPT], ed[EPT]; uint2 ee[EPT];
        const int e0 = cta * EPC + tid, nl0 = min(EPC, NE - cta * EPC) - tid;
        sfor<EPT>([&](auto I) { constexpr int i = I.v; ed[i] = -1;
            asm volatile("{.reg .pred p; setp.lt.s32 p,%2,%3; @p ld.global.u32 %0,[%1+%4];}" : "+r"(ed[i]) : "l"(p.dst + e0), "n"(i * NPT), "r"(nl0), "n"(i * NPT * 4)); });
        sfor<EPT>([&](auto I) { constexpr int i = I.v; es[i] = 0;
            asm volatile("{.reg .pred p; setp.lt.s32 p,%2,%3; @p ld.global.u32 %0,[%1+%4];}" : "+r"(es[i]) : "l"(p.src + e0), "n"(i * NPT), "r"(nl0), "n"(i * NPT * 4)); });
        sfor<EPT>([&](auto I) { constexpr int i = I.v;
            asm volatile("{.reg .pred p; setp.lt.s32 p,%3,%4; @p ld.global.v2.u32 {%0,%1},[%2+%5];}" : "=r"(ee[i].x), "=r"(ee[i].y) : "l"(p.ea + e0), "n"(i * NPT), "r"(nl0), "n"(i * NPT * 8)); });
        const uint32_t dbase = tid >= 384 ? ld_rlx(&p.cur[((cta % NSW) * NCL + min(tid - 384, NCL - 1)) * 8 + 1]) : 0;
        if (tid >= 256) {
            asm volatile("ld.relaxed.gpu.global.u64 %0,[%1];" : "=l"(epoch) : "l"(p.cnt + half * 16) : "memory");
            cbase = ld_rlx(&p.cur[(((tid >> 5) - 8) * NCL + cl) * 8 + 1]);
        }
        if (tid < 72) { sts32<M_CC>(sb + tid * 4, 0); sts32<M_GD>(sb + tid * 4, 0); }
        if (tid >= 96 && tid < 288) sts32<M_NC>(sb + (tid - 96) * 4, 0);
        if (tid >= 288 && tid < 320) sts32<M_SE + 640>(sb + (tid - 288) * 4, RTOT - 16);
        asm volatile("bar.sync 9,512;" ::: "memory");
        uint32_t rk[EPT], ec[EPT];
#pragma unroll
        for (int i = 0; i < EPT; i++) {
            ec[i] = (uint32_t)max(ed[i], 0) / RPC;
            rk[i] = atoms_inc(sb + (ed[i] >= 0 ? M_CC + ec[i] * 4 : M_SE + lane * 4));
        }
        if (tid < 448) asm volatile("bar.arrive 6,512;" ::: "memory");
        else {
            asm volatile("bar.sync 6,512;" ::: "memory");
            TSX(31, 448);
            if (tid == 448) { load_hw(); TSX(6, 448); }
        }
        uint32_t ad[EPT], as[EPT];
        asm volatile("bar.sync 11,512;" ::: "memory");
        TSX(28, 0);
#pragma unroll
        for (int i = 0; i < EPT; i++) {
            rk[i] += lds32<M_CO>(sb + ec[i] * 4);
            ad[i] = sb + ((max(ed[i], 0) * 6) & ~3u); as[i] = sb + ((es[i] * 6) & ~3u);
        }
#pragma unroll
        for (int i = 0; i < EPT; i++)
            asm volatile("{.reg .pred p; setp.ge.s32 p,%2,0; @p st.shared.u32 [%0+%3],%1;}"
                         ::"r"(sb + rk[i] * 4), "r"(((uint32_t)es[i] << 18) | (ec[i] << 8) | (ed[i] - ec[i] * RPC)), "r"(ed[i]), "n"(OFF_STM) : "memory");
        if (tid >= 384 && tid < 384 + NCL) asm volatile("red.shared.add.u32 [%0],%1;" ::"r"(sb + M_GD + (tid - 384) * 4), "r"(-dbase - lds32<M_CO - 384 * 4>(sb + tid * 4)) : "memory");
        mbar_wait(bars + BAR_POS * 8);
        TSX(22, 0);
        uint32_t pv[EPT][4];
#pragma unroll
        for (int i = 0; i < EPT; i++) { pv[i][0] = lds32<OFF_WQ>(ad[i]); pv[i][1] = lds32<OFF_WQ + 4>(ad[i]); pv[i][2] = lds32<OFF_WQ>(as[i]); pv[i][3] = lds32<OFF_WQ + 4>(as[i]); }
#pragma unroll
        for (int i = 0; i < EPT; i++) {
            const uint32_t sd = (ed[i] & 1) * 16, ss = (es[i] & 1) * 16;
            const uint2 q = geom(pv[i][0] >> sd, __funnelshift_rc(pv[i][0], pv[i][1], 16 + sd), pv[i][2] >> ss, __funnelshift_rc(pv[i][2], pv[i][3], 16 + ss));
            asm volatile("{.reg .pred p; setp.ge.s32 p,%5,0; @p st.shared.v4.u32 [%0+%6],{%1,%2,%3,%4};}"
                         ::"r"(sb + rk[i] * 16), "r"(ee[i].x), "r"(ee[i].y), "r"(q.x), "r"(q.y), "r"(ed[i]), "n"(OFF_RX) : "memory");
        }
        if (!(HV & 32)) { asm volatile("bar.sync 7,512;" ::: "memory"); copy_out(IC<EPT>{}, IC<NPT>{}, tid); }
    }
    const int wid = __shfl_sync(~0u, tid >> 5, 0), wg = wid >> 2, w = wid & 3, mt = wg & 1;
    const uint32_t xd = ((sb & 0x3ffff) >> 4) | 0x10000, wd = xd + mt * 2048;
    auto st_off = [&]() { uint32_t l; asm volatile("mov.u32 %0,%%laneid;" : "=r"(l)); return ((l >> 4) * 8 + (l & 7)) * 128 + (((w * 2 + ((l >> 3) & 1)) ^ (l & 7)) << 4); };
    if (wid < 8) {
        if (HV & 32) asm volatile("bar.arrive 7,512;" ::: "memory"); else asm volatile("bar.arrive 10,512;" ::: "memory");
        TS(20);
        float d[76]; uint32_t u[38];
        const uint32_t wr = sb + OFF_WR + mt * 32768, wq = sb + OFF_WQ + mt * 32768;
        sfor<4>([&](auto K) { constexpr int k = K.v;
            mbar_wait(bars + (BAR_H + k) * 8); mbar_wait(bars + (BAR_W2 + k) * 8);
            if (k == 0) TS(1);
            gemm_chunk<k == 0, OFF_WR + k * 8192, OFF_RH + k * ATOM>(d, wd, xd); });
        wg_wait<0>(); pin<76>(d);
        TS(3);
        bar_wg(wg);
        uint32_t stOff = st_off();
#pragma unroll
        for (int j = 0; j < 9; j++)
            stsm4t(wr + stOff + j * 2048, pack2(d[8 * j], d[8 * j + 1]), pack2(d[8 * j + 2], d[8 * j + 3]), pack2(d[8 * j + 4], d[8 * j + 5]), pack2(d[8 * j + 6], d[8 * j + 7]));
        stsm2t(wr + stOff + 9 * 2048, pack2(d[72], d[73]), pack2(d[74], d[75]));
        fence_async();
        __syncwarp();
        if (lane == 0) mbar_arrive(bars + BAR_B * 8);
        mbar_wait(bars + BAR_B * 8);
        mbar_wait(bars + (BAR_WH1 + 0) * 8);
        gemm_chunk<true, OFF_WQ, OFF_RH>(d, wd, xd);
        sfor<3>([&](auto K) { constexpr int k = K.v + 1;
            mbar_wait(bars + (BAR_WH1 + k) * 8);
            gemm_chunk<false, OFF_WQ + k * 8192, OFF_RH + k * ATOM>(d, wd, xd);
            wg_wait<1>();
            bar_wg(wg);
            if ((tid & 127) == 0) { mbar_expect(bars + (BAR_W1 + k) * 8, 8192); tma2d(wq + (k - 1) * 8192, &tmWe, half * 128 + mt * 64, (k ^ kx) * 64, bars + (BAR_W1 + k) * 8); } });
        wg_wait<0>(); pin<76>(d);
        TS(4);
#pragma unroll
        for (int i = 0; i < 38; i++) u[i] = pack2(d[2 * i], d[2 * i + 1]);
        sfor<4>([&](auto K) { constexpr int k = K.v;
            mbar_wait(bars + (BAR_W1 + k) * 8);
            gemm_chunk<k == 0, k == 0 ? OFF_RX : OFF_WQ + (k - 1) * 8192, OFF_RH + k * ATOM>(d, k == 0 ? xd + mt * 512 : wd, xd); });
        wg_wait<0>(); pin<76>(d);
        TS(5);
        asm volatile("bar.sync 5,256;" ::: "memory");
        if (tid == 0) asm volatile("mbarrier.arrive.relaxed.cluster.shared::cluster.b64 _,[%0];" ::"r"(peer + M_BAR + BAR_RDY * 8) : "memory");
        if (tid == 32) load_wf(0);
        sts128<OFF_PP>(sb + tid * 16, ~0u, ~0u, ~0u, ~0u);
        stOff = st_off();
        auto halfp = [&](int i) { return hmul2(pack2(d[i], d[i + 1]), 0x3f003f00u); };
#pragma unroll
        for (int j = 0; j < 9; j++) stsm4t(sb + mt * PL + stOff + j * 2048, halfp(8 * j), halfp(8 * j + 2), halfp(8 * j + 4), halfp(8 * j + 6));
        stsm2t(sb + mt * PL + stOff + 9 * 2048, halfp(72), halfp(74));
        asm volatile("bar.sync 0;" ::: "memory");
        load_edge_weights();
        {
#pragma unroll
            for (int i = 0; i < 38; i++) u[i] = hmul2(u[i], 0x3f003f00u);
            const uint32_t ca = sb + OFF_C + mt * ATOM + (tid & 127) * 16;
#pragma unroll
            for (int j = 0; j < 9; j++) sts128<0>(ca + j * 2048, u[4 * j], u[4 * j + 1], u[4 * j + 2], u[4 * j + 3]);
            asm volatile("st.shared.v2.u32 [%0],{%1,%2};" ::"r"(sb + OFF_C + mt * ATOM + 9 * 2048 + (tid & 127) * 8), "r"(u[36]), "r"(u[37]) : "memory");
        }
    } else if (wid < 15) {
        const int st = tid - 256;
        if (HV & 512) load_edge_weights();
        if (HV & 32) { asm volatile("bar.sync 7,512;" ::: "memory"); copy_out(IC<5>{}, IC<256>{}, st); }
        if (cbase == 0x9e3779b9u) sts32<M_NE + 8>(sb, cbase);
        asm volatile("bar.sync 10,%0;" ::"n"((HV & 32) ? 256 : 512) : "memory");
        TSX(2, 256);
        if (st == 0) {
            asm volatile("red.release.gpu.global.add.u64 [%0],1;" ::"l"(p.cnt + 32) : "memory");
            TSX(23, 256);
        }
        if (!(HV & 512)) load_edge_weights();
        int nl;
        {
            const int sw = wid - 8;
            uint32_t v, it = 0;
            do { v = ld_rlx(&p.cur[(sw * NCL + cl) * 8]) - cbase; } while ((v >> 24) != (NCTA + NSW - 1 - sw) / NSW && ++it < SPIN_LIMIT);
            nl = v & 0xffffffu; cbase += v;
            if (lane == 0) sts32<M_NL>(sb + sw * 4, nl);
        }
        if (st == 0) {
            const unsigned long long target = (epoch / NCL + 1) * NCTA;
            unsigned long long v; uint32_t it = 0;
            do { asm volatile("ld.acquire.gpu.global.u64 %0,[%1];" : "=l"(v) : "l"(p.cnt + 32) : "memory"); } while (v < target && ++it < SPIN_LIMIT);
        }
        asm volatile("bar.sync 8,%0;" ::"n"(NST) : "memory");
        const int nk = lane < NSW ? lds32<M_NL>(sb + lane * 4) : 0;
        const bool ovf = __any_sync(~0u, nk > SUB) || __reduce_add_sync(~0u, min(nk, SUB)) > ECAP;
        const int rbase = __reduce_add_sync(~0u, lane < wid - 8 ? (nk + 7) & ~7 : 0);
        if (half == 0 && lane == 0) p.cur[((wid - 8) * NCL + cl) * 8 + 1] = cbase;
        if (lane == 0) { asm volatile("fence.proxy.async.global;" ::: "memory"); mbar_expect(bars + BAR_REC * 8, ovf ? 0 : nl * 16); }
        TSX(18, 256);
        if (ovf) { if (st == 0) sts32<M_NE>(sb, ECAP + 1); }
        else {
            uint32_t mrun[IPT], rk[IPT];
            const uint32_t* gm = p.meta + cl * RCAP + (wid - 8) * SUB + lane;
            const int nr = nl - lane;
            const bool big = nl > (IPT - 2) * 32;
            sfor<IPT>([&](auto I) { constexpr int i = I.v;
                mrun[i] = 160 + lane;
                asm volatile("{.reg .pred p; setp.lt.s32 p,%2,%3; @p ld.global.cg.u32 %0,[%1+%4];}" : "+r"(mrun[i]) : "l"(gm), "n"(i * 32), "r"(nr), "n"(i * 128) : "memory"); });
            sfor<IPT>([&](auto I) { constexpr int i = I.v; if (i < IPT - 2 || big) rk[i] = atoms_inc(sb + M_NC + (mrun[i] & 0xff) * 4); });
            asm volatile("bar.sync 8,%0;" ::"n"(NST) : "memory");
            if (wid == 8) scan_nodes(sb, lane);
            mbar_wait(bars + BAR_BS * 8);
            if (lane == 0 && nl) asm volatile("cp.async.bulk.shared::cluster.global.mbarrier::complete_tx::bytes [%0],[%1],%2,[%3];"
                                              ::"r"(sb + OFF_REC + rbase * 16), "l"(p.rec + cl * RCAP + (wid - 8) * SUB), "r"(nl * 16), "r"(bars + BAR_REC * 8) : "memory");
            asm volatile("bar.sync 8,%0;" ::"n"(NST) : "memory");
            TSX(19, 256);
            sfor<IPT>([&](auto I) { constexpr int i = I.v; if (i < IPT - 2 || big) rk[i] = min(rk[i] + lds16<M_SE>(sb + (mrun[i] & 0xff) * 4), (uint32_t)RTOT - 1); });
            const uint32_t ro = (rbase + lane) * 16;
            sfor<IPT>([&](auto I) { constexpr int i = I.v;
                if (i < IPT - 2 || big) { sts32<OFF_META>(sb + rk[i] * 4, mrun[i]); sts16<OFF_IDX>(sb + rk[i] * 2, ro + i * 512); } });
            pad_records(sb, lds32<M_NE>(sb), st);
        }
        TSX(21, 256);
        asm volatile("bar.sync 0;" ::: "memory");
    } else {
        if (lane == 0) {
#pragma unroll
            for (int i = 0; i < NBAR; i++) if (i != BAR_POS) mbar_init(bars + i * 8, i == BAR_B ? 8 : i == BAR_E ? 16 : (i >= BAR_O && i < BAR_O + 4) ? 4 : i == BAR_REC ? NSW : (i > BAR_W1 && i < BAR_W1 + 4) ? 2 : 1);
            asm volatile("fence.mbarrier_init.release.cluster;" ::: "memory");
            mbar_expect(bars + BAR_M * 8, 2 * ATOM);
            mbar_expect(bars + BAR_PP * 8, 228 * 4);
        }
        __syncwarp();
        asm volatile("ld.relaxed.gpu.global.u64 %0,[%1];" : "=l"(epoch) : "l"(p.cnt + half * 16) : "memory");
        if (HV & 1024) load_edge_weights();
        asm volatile("bar.sync 6,512;" ::: "memory");
        {
            uint32_t gb[3];
#pragma unroll
            for (int i = 0; i < 3; i++) {
                const int c = min(lane + 32 * i, NCL - 1);
                asm volatile("{.reg .pred p; setp.lt.s32 p,%3,%4; @p atom.global.add.u32 %0,[%1],%2;}" : "=r"(gb[i])
                             : "l"(&p.cur[((cta % NSW) * NCL + c) * 8]), "r"(lds32<M_CC>(sb + c * 4) + (1u << 24)), "r"(lane + 32 * i), "n"(NCL) : "memory");
            }
            scan_clusters(sb, lane);
            asm volatile("bar.arrive 11,512;" ::: "memory");
#pragma unroll
            for (int i = 0; i < 3; i++) if (lane + 32 * i < NCL) asm volatile("red.shared.add.u32 [%0],%1;" ::"r"(sb + M_GD + (lane + 32 * i) * 4), "r"(gb[i]) : "memory");
        }
        TSX(9, 480);
        asm volatile("bar.sync 7,512;" ::: "memory");
        if (HV & 32) copy_out(IC<5>{}, IC<256>{}, tid - 256);
        if (!(HV & 1024)) load_edge_weights();
        asm volatile("bar.sync 10,%0;" ::"n"((HV & 32) ? 256 : 512) : "memory");
        if (lane == 0) {
#pragma unroll
            for (int k = 0; k < 4; k++) load_w(sb + OFF_WQ + k * 8192, 32768, &tmWh, half * 128, (k ^ kx) * 64, bars + (BAR_WH1 + k) * 8);
            load_w(sb + OFF_RX, 8192, &tmWe, half * 128, kx * 64, bars + (BAR_W1 + 0) * 8);
            mbar_wait(bars + BAR_B * 8);
            TSX(24, 480);
#pragma unroll
            for (int m = 0; m < 2; m++)
                asm volatile("cp.async.bulk.tensor.2d.global.shared::cta.bulk_group [%0,{%2,%3}],[%1];"
                             ::"l"((uint64_t)&tmB), "r"(sb + OFF_WR + m * 32768), "r"(half * 128 + m * 64), "r"(node0) : "memory");
            asm volatile("cp.async.bulk.commit_group;\ncp.async.bulk.wait_group 0;" ::: "memory");
            asm volatile("fence.proxy.async.global;" ::: "memory");
            TSX(25, 480);
            asm volatile("red.release.gpu.global.add.u64 [%0],1;" ::"l"(p.cnt + half * 16) : "memory");
            TSX(26, 480);
            mbar_arrive(bars + BAR_BS * 8);
            const unsigned long long target = (epoch / NCL + 1) * NCL;
            unsigned long long v; uint32_t it = 0;
            do { asm volatile("ld.acquire.gpu.global.u64 %0,[%1];" : "=l"(v) : "l"(p.cnt + half * 16) : "memory"); } while (v < target && ++it < SPIN_LIMIT);
        }
        if (lane == 0 && cta < 128) asm volatile("cp.async.bulk.prefetch.L2.global [%0],1024;" ::"l"(p.wh + 256 * 32 + cta * 64) : "memory");
        mbar_wait(bars + BAR_REC * 8);
        mbar_wait(bars + BAR_RDY * 8);
        TSX(27, 480);
        asm volatile("bar.sync 0;" ::: "memory");
    }
    const int ne = lds32<M_NE>(sb);
    const int slot = wid * 4 + (lane >> 3);
    const uint32_t l8x = l8 << 4;
    TS(10);
    if (ne > ECAP) {
        const uint2* we2 = (const uint2*)p.we + half * 32 + lane; const uint2 wxv = ((const uint2*)p.wx)[half * 32 + lane];
        for (int n = wid; n < RPC; n += 16) {
            const uint32_t ra = sb + (lane >> 4) * PL + n * 128 + ((((lane >> 1) ^ n) & 7) << 4) + (lane & 1) * 8;
            const uint32_t a0 = lds32<0>(ra), a1 = lds32<4>(ra);
            const int d = node0 + n;
            float m0 = 0.f, m1 = 0.f, m2 = 0.f, m3 = 0.f, qx = 0.f, qy = 0.f, qz = 0.f;
            for (int e0 = 0; e0 < NE; e0 += 32) {
                for (uint32_t hit = __ballot_sync(~0u, p.dst[e0 + lane] == d); hit; hit &= hit - 1) {
                    const int e = e0 + __ffs(hit) - 1, sr = p.src[e];
                    const uint2 ea = p.ea[e], bv = __ldcg((const uint2*)(p.B + (size_t)sr * 512 + half * 256) + lane);
                    const uint2 g = geom(p.pos[d * 3], p.pos[d * 3 + 1] | ((uint32_t)p.pos[d * 3 + 2] << 16), p.pos[sr * 3], p.pos[sr * 3 + 1] | ((uint32_t)p.pos[sr * 3 + 2] << 16));
                    const float fv[5] = {blo(g.x), blo(ea.x), bhi(ea.x), blo(ea.y), bhi(ea.y)};
                    float x0 = blo(bv.x), x1 = bhi(bv.x), x2 = blo(bv.y), x3 = bhi(bv.y);
#pragma unroll
                    for (int k = 0; k < 5; k++) { const uint2 wv = we2[(512 + k) * 64]; x0 += fv[k] * blo(wv.x); x1 += fv[k] * bhi(wv.x); x2 += fv[k] * blo(wv.y); x3 += fv[k] * bhi(wv.y); }
                    x0 = 0.5f * x0 + blo(a0); x1 = 0.5f * x1 + bhi(a0); x2 = 0.5f * x2 + blo(a1); x3 = 0.5f * x3 + bhi(a1);
                    x0 = fmaf(x0, tanh1(x0), x0); x1 = fmaf(x1, tanh1(x1), x1); x2 = fmaf(x2, tanh1(x2), x2); x3 = fmaf(x3, tanh1(x3), x3);
                    m0 += x0; m1 += x1; m2 += x2; m3 += x3;
                    const float cs = x0 * blo(wxv.x) + x1 * bhi(wxv.x) + x2 * blo(wxv.y) + x3 * bhi(wxv.y);
                    qx += cs * bhi(g.x); qy += cs * blo(g.y); qz += cs * bhi(g.y);
                }
            }
            const uint32_t o0 = pack2(0.5f * m0, 0.5f * m1), o1 = pack2(0.5f * m2, 0.5f * m3);
            sts32<0>(ra, o0); sts32<4>(ra, o1);
            asm volatile("st.async.weak.shared::cluster.mbarrier::complete_tx::bytes.v2.b32 [%0],{%1,%2},[%3];"
                         ::"r"(peer + OFF_MP + (ra - sb) - (lane >> 4) * (PL - ATOM)), "r"(o0), "r"(o1), "r"(peer + M_BAR + BAR_M * 8) : "memory");
#pragma unroll
            for (int o = 16; o; o >>= 1) { qx += __shfl_xor_sync(~0u, qx, o); qy += __shfl_xor_sync(~0u, qy, o); qz += __shfl_xor_sync(~0u, qz, o); }
            const uint32_t h0 = pack2(0.f, qx), h1 = pack2(qy, qz);
            const uint32_t v = lane == 0 ? h0 : lane == 1 ? h1 : lane == 2 ? pack2(0.f, qx - bhi(h0)) : lane == 3 ? pack2(qy - blo(h1), qz - bhi(h1)) : 0;
            if (lane < 16) sts32<OFF_P>(sb + n * 64 + lane * 4, v);
        }
    }
    const int T = ne > ECAP ? 0 : ne < 512 ? (ne + 63) / 64 * 4 : (ne + 15) / 16, TG = T <= 32 ? T >> 1 : (T >> 1) - LD;
    auto wg_start = [&](int g) { return g < 2 ? (g * TG) >> 1 : TG + (((g - 2) * (T - TG)) >> 1); };
    const int L = wg_start(wg + 1) - wg_start(wg), e0 = wg_start(wg) * 16 + (slot & 15) * L;
    const uint32_t sideOff = (RPC + slot) * 128 + l8x;
    uint32_t A[8], acc[8], pa = 0, pb = 0, dst = sideOff, cur = RPC;
    bool fl = true;
#pragma unroll
    for (int j = 0; j < 8; j++) acc[j] = 0;
    {
        const uint64_t Bb = (uint64_t)(p.B + half * 256 + l8 * 16);
        const uint32_t bLo = (uint32_t)Bb, bHi = (uint32_t)(Bb >> 32);
        const uint32_t poEnd = sb + (e0 + L) * 4;
        if (L > 0) {
            uint32_t po = sb + e0 * 4, pi = sb + e0 * 2, g[8];
            auto rowof = [&](uint32_t m) { const uint32_t n = m & 0xff; return n * 128 + (((n & 7) << 4) ^ l8x); };
            auto loadA = [&](uint32_t ra) { const uint4 u = lds128<0>(sb + ra), v = lds128<PL>(sb + ra);
                A[0] = u.x; A[1] = u.y; A[2] = u.z; A[3] = u.w; A[4] = v.x; A[5] = v.y; A[6] = v.z; A[7] = v.w; };
            auto gather = [&](uint32_t m) { const uint32_t lo = (m >> 9) + bLo; const uint4 u = ldg_row<0>(lo, bHi), v = ldg_row<128>(lo, bHi);
                g[0] = u.x; g[1] = u.y; g[2] = u.z; g[3] = u.w; g[4] = v.x; g[5] = v.y; g[6] = v.z; g[7] = v.w; };
            cur = lds32<OFF_META>(po); gather(cur);
            { const uint32_t ra = rowof(cur); loadA(ra); if (((lds32<OFF_META - 4>(po) ^ cur) & 0xff) != 0) dst = ra; }
            uint4 f = lds128<OFF_REC>(sb + lds16<OFF_IDX>(pi));
            uint32_t wn = lds32<OFF_META + 4>(po), ri = lds16<OFF_IDX + 2>(pi);
            auto step = [&](bool more) {
                uint32_t t[8];
#pragma unroll
                for (int j = 0; j < 8; j++) t[j] = (EV & 768) ? hfma2_lv(wf[0][j], f.x, g[j]) : (EV & 4) ? hfma2_l(wf[2][j], f.y, g[j]) : (EV & 8) ? hfma2_l(wf[4][j], f.z, g[j]) : hfma2_l(wf[0][j], f.x, g[j]);
                if ((EV & 256) && more) asm volatile("griddepcontrol.launch_dependents;" ::: "memory");
                if (more) gather(wn);
                if ((EV & 512) && more) asm volatile("griddepcontrol.launch_dependents;" ::: "memory");
                uint32_t cs = 0, rn = 0;
                if ((EV & 16) && more) rn = lds16<OFF_IDX + 4>(pi);
#pragma unroll
                for (int jj = 0; jj < 8; jj++) {
                    const int j = (EV & 32) ? (jj >> 1) + (jj & 1) * 4 : (EV & 64) ? 7 - jj : jj;
                    uint32_t y;
                    if (EV & 4) { y = hfma2_h(wf[3][j], f.y, t[j]); y = hfma2_l(wf[0][j], f.x, y); y = hfma2_h(wf[1][j], f.x, y); y = hfma2_l(wf[4][j], f.z, y); }
                    else if (EV & 8) { y = hfma2_l(wf[0][j], f.x, t[j]); y = hfma2_h(wf[1][j], f.x, y); y = hfma2_l(wf[2][j], f.y, y); y = hfma2_h(wf[3][j], f.y, y); }
                    else { y = hfma2_h(wf[1][j], f.x, t[j]); y = hfma2_l(wf[2][j], f.y, y); y = hfma2_h(wf[3][j], f.y, y); y = hfma2_l(wf[4][j], f.z, y); }
                    y = hfma2(y, 0x3f003f00u, A[j]);
                    const uint32_t m = hfma2(y, tanh2(y), y);
                    acc[j] = hfma2(m, 0x3f003f00u, acc[j]);
                    cs = jj == 0 ? hmul2(m, wx[j]) : hfma2(m, wx[j], cs);
                }
                cs = hsum2(cs); pa = hfma2(cs, f.z, pa); pb = hfma2(cs, f.w, pb);
                if (more) { f = lds128<OFF_REC>(sb + ri); ri = (EV & 16) ? rn : lds16<OFF_IDX + 4>(pi); }
                fl = ((wn ^ cur) & 0xff) != 0;
                if (fl) {
                    const uint32_t od = dst;
                    cur = wn; dst = rowof(wn); loadA(dst);
                    sts128<0>(sb + od, acc[0], acc[1], acc[2], acc[3]); sts128<PL>(sb + od, acc[4], acc[5], acc[6], acc[7]); sts64<OFF_P>(sb + (od >> 1), pa, pb);
                    send16<0>(peer, od, acc[0], acc[1], acc[2], acc[3]); send16<ATOM>(peer, od, acc[4], acc[5], acc[6], acc[7]);
                    const uint4 z0 = lds128<OFF_ZERO>(sb), z1 = lds128<OFF_ZERO + 16>(sb); const uint2 z2 = lds64<OFF_ZERO + 32>(sb);
                    acc[0] = z0.x; acc[1] = z0.y; acc[2] = z0.z; acc[3] = z0.w; acc[4] = z1.x; acc[5] = z1.y; acc[6] = z1.z; acc[7] = z1.w;
                    pa = z2.x; pb = z2.y;
                }
            };
#pragma unroll 1
            while (po + 4 < poEnd) { step(true); wn = lds32<OFF_META + 8>(po); po += 4; pi += 2; }
            step(false);
        }
        TS(11);
        __syncwarp();
        if (lane == 0) mbar_arrive(bars + BAR_E * 8);
    }
    const bool pend = !fl && (cur & 0xff) != RPC;
    if (pend && dst == sideOff) { sts128<0>(sb + dst, acc[0], acc[1], acc[2], acc[3]); sts128<PL>(sb + dst, acc[4], acc[5], acc[6], acc[7]); sts64<OFF_P>(sb + (dst >> 1), pa, pb); }
#pragma unroll
    for (int i = 0; i < 3; i++) {
        const int n = slot + i * NSLOT;
        const uint32_t se = lds32<M_SE>(sb + n * 4);
        if (n < RPC && ne <= ECAP && (se & 0xffffu) == (se >> 16)) {
            const uint32_t a = n * 128 + l8x;
            sts128<0>(sb + a, 0, 0, 0, 0); sts128<PL>(sb + a, 0, 0, 0, 0); sts64<OFF_P>(sb + (a >> 1), 0, 0);
            send16<0>(peer, a, 0, 0, 0, 0); send16<ATOM>(peer, a, 0, 0, 0, 0);
        }
    }
    __syncwarp();
    if (pend && dst != sideOff) {
        const int nodeEnd = lds16<M_SE + 2>(sb + (cur & 0xff) * 4);
        int e = e0 + L, t = slot;
        uint32_t sa = sideOff;
        do {
            sa += 128; t++; e += wg_start((t >> 4) + 1) - wg_start(t >> 4);
            uint2 b2; uint32_t it = 0;
            do { asm volatile("ld.volatile.shared.v2.u32 {%0,%1},[%2+%3];" : "=r"(b2.x), "=r"(b2.y) : "r"(sb + (sa >> 1)), "n"(OFF_P) : "memory"); } while (b2.y == ~0u && ++it < SPIN_LIMIT);
            const uint4 b0 = lds128<0>(sb + sa), b1 = lds128<PL>(sb + sa);
            acc[0] = hadd2(acc[0], b0.x); acc[1] = hadd2(acc[1], b0.y); acc[2] = hadd2(acc[2], b0.z); acc[3] = hadd2(acc[3], b0.w);
            acc[4] = hadd2(acc[4], b1.x); acc[5] = hadd2(acc[5], b1.y); acc[6] = hadd2(acc[6], b1.z); acc[7] = hadd2(acc[7], b1.w);
            pa = hadd2(pa, b2.x); pb = hadd2(pb, b2.y);
        } while (e < nodeEnd);
        sts128<0>(sb + dst, acc[0], acc[1], acc[2], acc[3]); sts128<PL>(sb + dst, acc[4], acc[5], acc[6], acc[7]); sts64<OFF_P>(sb + (dst >> 1), pa, pb);
    }
    fence_async();
    if (pend && dst != sideOff) { send16<0>(peer, dst, acc[0], acc[1], acc[2], acc[3]); send16<ATOM>(peer, dst, acc[4], acc[5], acc[6], acc[7]); }
    if (wid < 8) {
        const uint32_t stg = sb + OFF_C + mt * ATOM;
        float d[76];
#pragma unroll
        for (int j = 0; j < 10; j++) {
            uint4 c;
            if (j < 9) c = lds128<0>(stg + j * 2048 + (tid & 127) * 16);
            else { c.x = lds32<0>(stg + j * 2048 + (tid & 127) * 8); c.y = lds32<4>(stg + j * 2048 + (tid & 127) * 8); }
            d[8 * j] = blo(c.x); d[8 * j + 1] = bhi(c.x); d[8 * j + 2] = blo(c.y); d[8 * j + 3] = bhi(c.y);
            if (j < 9) { d[8 * j + 4] = blo(c.z); d[8 * j + 5] = bhi(c.z); d[8 * j + 6] = blo(c.w); d[8 * j + 7] = bhi(c.w); }
        }
        pin<76>(d);
        TS(8);
        asm volatile("bar.sync 0;" ::: "memory");
        TS(12);
        if ((TV & 1) && mt == 1) asm volatile("bar.sync 5,256;" ::: "memory");
        mbar_wait(bars + (BAR_WH2 + mt * 2) * 8);
        TS(7);
        gemm_chunk<false, OFF_WF, 0>(d, wd, xd);
        gemm_chunk<false, OFF_WF + 8192, PL>(d, wd, xd);
        mbar_wait(bars + (BAR_WH2 + mt * 2 + 1) * 8);
        mbar_wait(bars + BAR_M * 8);
        fence_async();
        TS(29);
        if (!(TV & 1) && mt == 1) asm volatile("bar.sync 5,256;" ::: "memory");
        gemm_chunk<false, OFF_WF + 16384, OFF_MP>(d, wd, xd);
        gemm_chunk<false, OFF_WF + 24576, OFF_MP + ATOM>(d, wd, xd);
        if (mt == 0) asm volatile("bar.arrive 5,256;" ::: "memory");
        wg_wait<0>();
        pin<76>(d);
        TS(13); TSX(17, 128);
        const uint32_t stOff = st_off();
        auto silu2 = [&](int i) { const float y0 = d[i], y1 = d[i + 1]; return pack2(fmaf(y0, tanh1(y0), y0), fmaf(y1, tanh1(y1), y1)); };
#pragma unroll
        for (int j = 0; j < 5; j++) stsm4t(stg + stOff + j * 2048, silu2(8 * j), silu2(8 * j + 2), silu2(8 * j + 4), silu2(8 * j + 6));
        __syncwarp();
        if (lane == 0) mbar_arrive(bars + (BAR_O + mt * 2) * 8);
#pragma unroll
        for (int j = 5; j < 9; j++) stsm4t(stg + stOff + j * 2048, silu2(8 * j), silu2(8 * j + 2), silu2(8 * j + 4), silu2(8 * j + 6));
        stsm2t(stg + stOff + 9 * 2048, silu2(72), silu2(74));
        __syncwarp();
        if (lane == 0) mbar_arrive(bars + (BAR_O + mt * 2 + 1) * 8);
        TS(15); TSX(16, 128);
    } else {
        const int t = tid - 256, cr = t >> 3, cc = t & 7;
        const int nrow = min(RPC, NN - node0);
        const size_t go = (size_t)(node0 + cr) * 32 + half * 16 + cc;
        if (wid > 12 && lane == 0) { mbar_wait(bars + BAR_E * 8); load_wf(wid - 12); }
        __syncwarp();
        asm volatile("bar.sync 0;" ::: "memory");
        if (TV & 2) mbar_wait(bars + (BAR_WH2 + 1) * 8);
        if (TV & 4) mbar_wait(bars + (BAR_WH2 + 3) * 8);
        uint4 hv[2][2][3];
#pragma unroll
        for (int m = 0; m < 2; m++)
#pragma unroll
            for (int q = 0; q < 2; q++)
#pragma unroll
                for (int i = 0; i < 3; i++)
                    if (cr + 32 * i < 80 && 80 * q + 32 * i + cr < nrow) hv[m][q][i] = __ldcg(p.h + go + (80 * q + 32 * i) * 32 + m * 8);
        const bool pown = t < 228 && node0 * 3 + half * 228 + t < NN * 3;
        const float pos0 = pown ? blo(__ldcg(p.pos + node0 * 3 + half * 228 + t)) : 0.f;
        mbar_wait(bars + BAR_M * 8);
        float ps[2] = {0.f, 0.f};
        if (t < 228) {
#pragma unroll
            for (int k = 0; k < 2; k++) {
                const int n = (k ^ half ^ 1) * 76 + t / 3;
                const uint32_t a = sb + n * 64 + (t % 3) * 2 + 2;
#pragma unroll
                for (int l = 0; l < 8; l++) ps[k] += blo(lds16<OFF_P>(a + (((l + (n >> 1)) & 7) << 3)));
                if (k == 0) asm volatile("st.async.weak.shared::cluster.mbarrier::complete_tx::bytes.f32 [%0],%1,[%2];"
                                         ::"r"(peer + OFF_PP + t * 4), "f"(ps[0]), "r"(peer + M_BAR + BAR_PP * 8) : "memory");
            }
        }
#pragma unroll
        for (int m = 0; m < 2; m++)
#pragma unroll
            for (int q = 0; q < 2; q++) {
                mbar_wait(bars + (BAR_O + m * 2 + q) * 8);
#pragma unroll
                for (int i = 0; i < 3; i++)
                    if (cr + 32 * i < 80 && 80 * q + 32 * i + cr < nrow) {
                        const uint4 v = lds128<OFF_C>(sb + m * ATOM + (80 * q + 32 * i + cr) * 128 + ((cc ^ (cr & 7)) << 4)), hh = hv[m][q][i];
                        p.out_h[go + (80 * q + 32 * i) * 32 + m * 8] = make_uint4(hadd2(hh.x, v.x), hadd2(hh.y, v.y), hadd2(hh.z, v.z), hadd2(hh.w, v.w));
                    }
            }
        mbar_wait(bars + BAR_PP * 8);
        if (pown) ((unsigned short*)(p.out_h + NN * 32))[node0 * 3 + half * 228 + t] = (unsigned short)pack2(pos0 + ps[1] + __uint_as_float(lds32<OFF_PP>(sb + t * 4)), 0.f);
        TSX(14, 256);
    }
}

typedef CUresult (*EncodeFn)(CUtensorMap*, CUtensorMapDataType, cuuint32_t, void*, const cuuint64_t*, const cuuint64_t*,
                             const cuuint32_t*, const cuuint32_t*, CUtensorMapInterleave, CUtensorMapSwizzle,
                             CUtensorMapL2promotion, CUtensorMapFloatOOBfill);

void make_map(EncodeFn fn, CUtensorMap* m, void* ptr, uint64_t rows, uint32_t boxRows) {
    const cuuint64_t dims[2] = {256, rows}, strides[1] = {512};
    const cuuint32_t box[2] = {64, boxRows}, es[2] = {1, 1};
    fn(m, CU_TENSOR_MAP_DATA_TYPE_BFLOAT16, 2, ptr, dims, strides, box, es, CU_TENSOR_MAP_INTERLEAVE_NONE,
       CU_TENSOR_MAP_SWIZZLE_128B, CU_TENSOR_MAP_L2_PROMOTION_L2_256B, CU_TENSOR_MAP_FLOAT_OOB_FILL_NONE);
}

}

extern "C" void kernel_launch(void* const* d_in, const int* in_sizes, int n_in, void* d_out, int out_size) {
    static EncodeFn enc = nullptr;
    static char* bptr = nullptr;
    static void* sym[4];
    if (!enc) {
        void* f = nullptr; cudaDriverEntryPointQueryResult q;
        cudaGetDriverEntryPoint("cuTensorMapEncodeTiled", &f, cudaEnableDefault, &q);
        enc = (EncodeFn)f;
        cudaFuncSetAttribute(egnn_kernel, cudaFuncAttributeMaxDynamicSharedMemorySize, SMEM_TOTAL);
        cudaGetSymbolAddress(&sym[0], g_cur); cudaGetSymbolAddress(&sym[1], g_cnt); cudaGetSymbolAddress(&sym[2], g_rec); cudaGetSymbolAddress(&sym[3], g_meta);
        void* b = nullptr; cudaGetSymbolAddress(&b, g_B);
        bptr = (char*)b;
        if (((uint64_t)bptr >> 32) != (((uint64_t)bptr + (size_t)NCL * RPC * 512 - 1) >> 32)) bptr += (size_t)NCL * RPC * 512;
    }
    CUtensorMap tmH, tmWe, tmWh, tmB;
    make_map(enc, &tmH, d_in[0], NN, RPC);
    make_map(enc, &tmWe, d_in[5], 517, 64);
    make_map(enc, &tmWh, d_in[7], 512, 64);
    make_map(enc, &tmB, bptr, NCL * RPC, RPC);
    Params p;
    p.h = (const uint4*)d_in[0]; p.pos = (const unsigned short*)d_in[1]; p.ea = (const uint2*)d_in[2];
    p.src = (const int*)d_in[3]; p.dst = (const int*)d_in[4]; p.we = (const uint4*)d_in[5]; p.wx = (const uint4*)d_in[6]; p.wh = (const uint4*)d_in[7];
    p.out_h = (uint4*)d_out; p.B = bptr; p.cur = (uint32_t*)sym[0]; p.cnt = (unsigned long long*)sym[1]; p.rec = (uint4*)sym[2]; p.meta = (uint32_t*)sym[3];
    egnn_kernel<<<NCTA, NTH, SMEM_TOTAL, cudaStreamPerThread>>>(p, tmH, tmWe, tmWh, tmB);
}
```
